```python
import torch

def _softmax(x, axis=-1):
    return torch.softmax(x, dim=axis)

def _gelu(x):
    return torch.nn.functional.gelu(x, approximate='tanh')

def _silu(x):
    return torch.nn.functional.silu(x)

def _sigmoid(x):
    return torch.sigmoid(x)

def _layernorm(x, axis=-1, eps=1e-05):
    m = x.mean(dim=axis, keepdim=True)
    v = x.var(dim=axis, keepdim=True, unbiased=False)
    return (x - m) / torch.sqrt(v + eps)

def _scatter_add(tgt, idx, src, axis=0):
    return tgt.clone().index_add_(axis, idx, src)

def _segment_sum(src, seg, n):
    out = torch.zeros((n,) + src.shape[1:], dtype=src.dtype)
    return out.index_add_(0, seg, src)

def _pad(x, pw):
    flat = tuple((v for pair in reversed(pw) for v in pair))
    return torch.nn.functional.pad(x, flat)
kernel_name = 'gated_mix__memory_aug_recurrent_mem_tr__swiglu_ffn__prompt'

def setup_inputs():

    _w = lambda a: (lambda t: t.to(torch.bfloat16) if t.is_floating_point() else t)(torch.as_tensor(a))

    def _A_setup():
        B, S, Dm = (1, 2048, 512)
        H, Dh = (32, 128)
        M, seg = (8, 32)
        seg = min(seg, S)
        S = S // seg * seg
        return {'x': _w((lambda *s: torch.randn(*s, dtype=torch.bfloat16) * 0.05)(B, S, Dm)), 'mem0': _w((lambda *s: torch.randn(*s, dtype=torch.bfloat16) * 0.4)(B, M, Dm)), 'Wq': _w((lambda *s: torch.randn(*s, dtype=torch.bfloat16) * 6.4)(Dm, H, Dh) * Dm ** (-0.5)), 'Wk': _w((lambda *s: torch.randn(*s, dtype=torch.bfloat16) * 6.4)(Dm, H, Dh) * Dm ** (-0.5)), 'Wv': _w((lambda *s: torch.randn(*s, dtype=torch.bfloat16) * 0.4)(Dm, H, Dh) * Dm ** (-0.5)), 'Wo': _w((lambda *s: torch.randn(*s, dtype=torch.bfloat16) * 0.4)(H, Dh, Dm) * (H * Dh) ** (-0.5)), 'seg_len': seg}
    _A_in = _A_setup()

    def _B_setup():
        B, S, D, F = (1, 2048, 512, 1376)
        return {'x': _w((lambda *s: torch.randn(*s, dtype=torch.bfloat16) * 0.05)(B, S, D)), 'w_gate': _w((lambda *s: torch.randn(*s, dtype=torch.bfloat16) * 0.05)(D, F)), 'w_up': _w((lambda *s: torch.randn(*s, dtype=torch.bfloat16) * 0.05)(D, F)), 'w_down': _w((lambda *s: torch.randn(*s, dtype=torch.bfloat16) * 0.05)(F, D))}
    _B_in = _B_setup()
    return {'A_x': _A_in['x'], 'A_mem0': _A_in['mem0'], 'A_Wq': _A_in['Wq'], 'A_Wk': _A_in['Wk'], 'A_Wv': _A_in['Wv'], 'A_Wo': _A_in['Wo'], 'A_seg_len': _A_in['seg_len'], 'B_x': _B_in['x'], 'B_w_gate': _B_in['w_gate'], 'B_w_up': _B_in['w_up'], 'B_w_down': _B_in['w_down'], 'gate_w': _w((lambda *s: torch.randn(*s, dtype=torch.bfloat16) * 0.05)(512) * 16.0)}

def reference(A_x, A_mem0, A_Wq, A_Wk, A_Wv, A_Wo, A_seg_len, B_x, B_w_gate, B_w_up, B_w_down, gate_w):

    def _A_ref(x, mem0, Wq, Wk, Wv, Wo, seg_len):
        B, S, Dm = x.shape
        H, Dh = (Wq.shape[1], Wq.shape[2])
        M = mem0.shape[1]
        scale = Dh ** (-0.5)
        n_seg = S // seg_len
        L = M + seg_len
        idx = torch.arange(L)
        mask = (idx[:, None] < M) | (idx[:, None] >= idx[None, :])
        mem = mem0
        outs = []
        for s in range(n_seg):
            xs = x[:, s * seg_len:(s + 1) * seg_len, :].clone()
            h = torch.concatenate([mem, xs], axis=1)
            q = torch.einsum('btd,dhe->bhte', h, Wq)
            k = torch.einsum('btd,dhe->bhte', h, Wk)
            v = torch.einsum('btd,dhe->bhte', h, Wv)
            scores = torch.einsum('bhqe,bhke->bhqk', q, k) * scale
            scores = torch.where(mask[None, None], scores, -1000000000.0)
            p = _softmax(scores, axis=-1)
            o = torch.einsum('bhqk,bhke->bhqe', p, v)
            o = torch.einsum('bhte,hed->btd', o, Wo)
            mem = o[:, :M, :].clone()
            outs.append(o[:, M:, :])
        return torch.concatenate(outs, axis=1)

    def _B_ref(x, w_gate, w_up, w_down):
        g = _silu(x @ w_gate)
        u = x @ w_up
        return g * u @ w_down
    x = A_x
    g = _sigmoid((x * gate_w).sum(-1, keepdims=True))
    a = _A_ref(x, A_mem0, A_Wq, A_Wk, A_Wv, A_Wo, A_seg_len)
    b = _B_ref(x, B_w_gate, B_w_up, B_w_down)
    return g * a + (1 - g) * b
```

```cpp
#include <cuda_runtime.h>
#include <cuda_bf16.h>
#include <cuda.h>
#include <stdint.h>

#define DEVI __device__ __forceinline__

namespace {

constexpr int NSEG = 64;

DEVI uint32_t smem_u32(const void* p) { return (uint32_t)__cvta_generic_to_shared(p); }
DEVI uint32_t mapa(uint32_t a, uint32_t r) { uint32_t d; asm("mapa.shared::cluster.u32 %0, %1, %2;" : "=r"(d) : "r"(a), "r"(r)); return d; }
DEVI void mbar_init(uint32_t a, uint32_t c) { asm volatile("mbarrier.init.shared::cta.b64 [%0], %1;" :: "r"(a), "r"(c) : "memory"); }
DEVI void mbar_expect(uint32_t a, uint32_t tx) { asm volatile("mbarrier.arrive.expect_tx.shared::cta.b64 _, [%0], %1;" :: "r"(a), "r"(tx) : "memory"); }
DEVI void mbar_arrive(uint32_t a) { asm volatile("mbarrier.arrive.shared::cta.b64 _, [%0];" :: "r"(a) : "memory"); }
DEVI void mbar_arrive_remote(uint32_t a) { asm volatile("mbarrier.arrive.relaxed.cluster.shared::cluster.b64 _, [%0];" :: "r"(a) : "memory"); }
DEVI uint32_t mbar_try(uint32_t a, uint32_t ph) {
    uint32_t ok;
    asm volatile("{.reg .pred p; mbarrier.try_wait.parity.shared::cta.b64 p, [%1], %2; selp.u32 %0,1,0,p;}" : "=r"(ok) : "r"(a), "r"(ph) : "memory");
    return ok;
}
DEVI uint32_t mbar_test(uint32_t a, uint32_t ph) {
    uint32_t ok;
    asm volatile("{.reg .pred p; mbarrier.test_wait.parity.shared::cta.b64 p, [%1], %2; selp.u32 %0,1,0,p;}" : "=r"(ok) : "r"(a), "r"(ph) : "memory");
    return ok;
}
DEVI void mbar_finish(uint32_t ok, uint32_t a, uint32_t ph) {
    asm volatile(
        "{\n.reg .pred p, q; .reg .u32 n;\n"
        "setp.ne.u32 p, %0, 0;\n"
        "mov.u32 n, 0;\n"
        "RETRY:\n"
        "@!p mbarrier.try_wait.parity.shared::cta.b64 p, [%1], %2;\n"
        "add.u32 n, n, 1;\n"
        "setp.lt.and.u32 q, n, 524288, !p;\n"
        "@q bra RETRY;\n"
        "@!p st.shared.u32 [n], n;\n"
        "}\n" :: "r"(ok), "r"(a), "r"(ph) : "memory");
}
DEVI void mbar_wait(uint32_t a, uint32_t ph) {
    asm volatile(
        "{\n.reg .pred p, q; .reg .u32 n;\n"
        "mov.u32 n, 0;\n"
        "RETRY:\n"
        "mbarrier.try_wait.parity.shared::cta.b64 p, [%0], %1;\n"
        "add.u32 n, n, 1;\n"
        "setp.lt.and.u32 q, n, 524288, !p;\n"
        "@q bra RETRY;\n"
        "@!p st.shared.u32 [n], n;\n"
        "}\n" :: "r"(a), "r"(ph) : "memory");
}
DEVI void sched_fence(uint32_t v) { asm volatile("{.reg .pred p; .reg .u32 t; and.b32 t, %0, 8; setp.ne.u32 p, t, 0; SELF: @p st.volatile.shared.u32 [%0], t; @p bra.uni SELF;}" :: "r"(v) : "memory"); }
DEVI uint32_t clock_lo() { uint64_t c; asm volatile("mov.u64 %0, %%clock64;" : "=l"(c)); return (uint32_t)c; }
DEVI uint32_t opaque(uint32_t v) { return __shfl_sync(0xffffffffu, v, threadIdx.x & 31); }
DEVI void bar_sync(int id, int n) { asm volatile("bar.sync %0, %1;" :: "r"(id), "r"(n) : "memory"); }
DEVI void bar_arrive(int id, int n) { asm volatile("bar.arrive %0, %1;" :: "r"(id), "r"(n) : "memory"); }
DEVI void cluster_sync() { asm volatile("barrier.cluster.arrive.aligned; barrier.cluster.wait.aligned;" ::: "memory"); }
DEVI void cluster_arrive_relaxed() { asm volatile("barrier.cluster.arrive.relaxed.aligned;" ::: "memory"); }
DEVI void cluster_wait() { asm volatile("barrier.cluster.wait.aligned;" ::: "memory"); }
DEVI void prefetch_map(const CUtensorMap* tm) { asm volatile("prefetch.tensormap [%0];" :: "l"(tm) : "memory"); }
DEVI void fence_async_smem() { asm volatile("fence.proxy.async.shared::cta;" ::: "memory"); }
DEVI void st_async1(uint32_t a, uint32_t m, uint32_t v) { asm volatile("st.async.weak.shared::cluster.mbarrier::complete_tx::bytes.b32 [%0], %2, [%1];" :: "r"(a), "r"(m), "r"(v) : "memory"); }
DEVI void st_async2(uint32_t a, uint32_t m, uint32_t v0, uint32_t v1) { asm volatile("st.async.weak.shared::cluster.mbarrier::complete_tx::bytes.v2.b32 [%0], {%2,%3}, [%1];" :: "r"(a), "r"(m), "r"(v0), "r"(v1) : "memory"); }
DEVI void st_async4(uint32_t a, uint32_t m, uint32_t v0, uint32_t v1, uint32_t v2, uint32_t v3) {
    asm volatile("st.async.weak.shared::cluster.mbarrier::complete_tx::bytes.v4.b32 [%0], {%2,%3,%4,%5}, [%1];" :: "r"(a), "r"(m), "r"(v0), "r"(v1), "r"(v2), "r"(v3) : "memory");
}
DEVI void sts1(uint32_t a, uint32_t v) { asm volatile("st.shared.b32 [%0], %1;" :: "r"(a), "r"(v) : "memory"); }
DEVI void sts2(uint32_t a, uint32_t v0, uint32_t v1) { asm volatile("st.shared.v2.b32 [%0], {%1,%2};" :: "r"(a), "r"(v0), "r"(v1) : "memory"); }
DEVI void sts4(uint32_t a, uint32_t v0, uint32_t v1, uint32_t v2, uint32_t v3) { asm volatile("st.shared.v4.b32 [%0], {%1,%2,%3,%4};" :: "r"(a), "r"(v0), "r"(v1), "r"(v2), "r"(v3) : "memory"); }
DEVI void lds4f(float2& u, float2& v, uint32_t a) { asm volatile("ld.shared.v4.f32 {%0,%1,%2,%3}, [%4];" : "=f"(u.x), "=f"(u.y), "=f"(v.x), "=f"(v.y) : "r"(a) : "memory"); }
DEVI uint32_t lds1(uint32_t a) { uint32_t v; asm volatile("ld.shared.b32 %0, [%1];" : "=r"(v) : "r"(a) : "memory"); return v; }
DEVI float2 lds2f(uint32_t a) { float2 v; asm volatile("ld.shared.v2.f32 {%0,%1}, [%2];" : "=f"(v.x), "=f"(v.y) : "r"(a) : "memory"); return v; }
DEVI void ldsm4(uint32_t (&r)[4], uint32_t a) { asm volatile("ldmatrix.sync.aligned.m8n8.x4.shared.b16 {%0,%1,%2,%3}, [%4];" : "=r"(r[0]), "=r"(r[1]), "=r"(r[2]), "=r"(r[3]) : "r"(a) : "memory"); }
DEVI void ldsm4t(uint32_t (&r)[4], uint32_t a) { asm volatile("ldmatrix.sync.aligned.m8n8.x4.trans.shared.b16 {%0,%1,%2,%3}, [%4];" : "=r"(r[0]), "=r"(r[1]), "=r"(r[2]), "=r"(r[3]) : "r"(a) : "memory"); }
DEVI uint32_t mbar_try_addr(uint32_t bar, uint32_t ph, uint32_t addr, uint32_t alt) {
    uint32_t r;
    asm volatile("{.reg .pred p; mbarrier.try_wait.parity.shared::cta.b64 p, [%1], %2; selp.u32 %0, %3, %4, p;}"
        : "=r"(r) : "r"(bar), "r"(ph), "r"(addr), "r"(alt) : "memory");
    return r;
}
DEVI void bar_arrive_if_eq(int id, int n, uint32_t a, uint32_t b) {
    asm volatile("{.reg .pred p; setp.eq.u32 p, %2, %3; @p bar.arrive %0, %1;}" :: "r"(id), "r"(n), "r"(a), "r"(b) : "memory");
}
DEVI void bar_sync_if_eq(int id, int n, uint32_t a, uint32_t b) {
    asm volatile("{.reg .pred p; setp.eq.u32 p, %2, %3; @p bar.sync %0, %1;}" :: "r"(id), "r"(n), "r"(a), "r"(b) : "memory");
}
DEVI void st_tagged(void* a, uint32_t w0, uint32_t w1, uint32_t tag) {
    asm volatile("{.reg .b64 u, v; mov.b64 u, {%1,%3}; mov.b64 v, {%2,%3}; st.relaxed.gpu.global.v2.b64 [%0], {u, v};}" :: "l"(a), "r"(w0), "r"(w1), "r"(tag) : "memory");
}
DEVI uint4 ld_tagged(const void* a) {
    uint4 r;
    asm volatile("{.reg .b64 u, v; ld.relaxed.gpu.global.v2.b64 {u, v}, [%4]; mov.b64 {%0,%1}, u; mov.b64 {%2,%3}, v;}" : "=r"(r.x), "=r"(r.y), "=r"(r.z), "=r"(r.w) : "l"(a) : "memory");
    return r;
}
DEVI uint64_t ld_relaxed64(const void* a) { uint64_t v; asm volatile("ld.relaxed.gpu.global.b64 %0, [%1];" : "=l"(v) : "l"(a) : "memory"); return v; }
DEVI void st_relaxed64(void* a, uint32_t lo, uint32_t hi) {
    asm volatile("{.reg .b64 v; mov.b64 v, {%1,%2}; st.relaxed.gpu.global.b64 [%0], v;}" :: "l"(a), "r"(lo), "r"(hi) : "memory");
}
template <class T> DEVI void pin(T*& p) { asm volatile("" : "+l"(p)); }
DEVI void pin(uint32_t& v) { asm volatile("" : "+r"(v)); }
DEVI void pin(float& v) { asm volatile("" : "+f"(v)); }
DEVI void fault_if(bool c) { if (c) asm volatile("st.shared.u32 [%0], %0;" :: "r"(0x80000u) : "memory"); }
DEVI void stsm4(uint32_t a, uint32_t r0, uint32_t r1, uint32_t r2, uint32_t r3) { asm volatile("stmatrix.sync.aligned.m8n8.x4.shared.b16 [%0], {%1,%2,%3,%4};" :: "r"(a), "r"(r0), "r"(r1), "r"(r2), "r"(r3) : "memory"); }
DEVI void stsm2(uint32_t a, uint32_t r0, uint32_t r1) { asm volatile("stmatrix.sync.aligned.m8n8.x2.shared.b16 [%0], {%1,%2};" :: "r"(a), "r"(r0), "r"(r1) : "memory"); }
DEVI void mma16816(float (&d)[4], uint32_t a0, uint32_t a1, uint32_t a2, uint32_t a3, uint32_t b0, uint32_t b1) {
    asm volatile("mma.sync.aligned.m16n8k16.row.col.f32.bf16.bf16.f32 {%0,%1,%2,%3}, {%4,%5,%6,%7}, {%8,%9}, {%0,%1,%2,%3};"
        : "+f"(d[0]), "+f"(d[1]), "+f"(d[2]), "+f"(d[3]) : "r"(a0), "r"(a1), "r"(a2), "r"(a3), "r"(b0), "r"(b1));
}
DEVI void mma16816(float (&d)[4], const uint32_t (&a)[4], uint32_t b0, uint32_t b1) { mma16816(d, a[0], a[1], a[2], a[3], b0, b1); }
DEVI void mma16816z(float (&d)[4], uint32_t a0, uint32_t a1, uint32_t a2, uint32_t a3, uint32_t b0, uint32_t b1) {
    asm volatile("mma.sync.aligned.m16n8k16.row.col.f32.bf16.bf16.f32 {%0,%1,%2,%3}, {%4,%5,%6,%7}, {%8,%9}, {%10,%10,%10,%10};"
        : "=f"(d[0]), "=f"(d[1]), "=f"(d[2]), "=f"(d[3]) : "r"(a0), "r"(a1), "r"(a2), "r"(a3), "r"(b0), "r"(b1), "f"(0.f));
}
DEVI void mma16816z(float (&d)[4], const uint32_t (&a)[4], uint32_t b0, uint32_t b1) { mma16816z(d, a[0], a[1], a[2], a[3], b0, b1); }
DEVI void mma1688(float (&d)[4], uint32_t a0, uint32_t a1, uint32_t b0) {
    asm volatile("mma.sync.aligned.m16n8k8.row.col.f32.bf16.bf16.f32 {%0,%1,%2,%3}, {%4,%5}, {%6}, {%0,%1,%2,%3};"
        : "+f"(d[0]), "+f"(d[1]), "+f"(d[2]), "+f"(d[3]) : "r"(a0), "r"(a1), "r"(b0));
}
DEVI void mma1688z(float (&d)[4], uint32_t a0, uint32_t a1, uint32_t b0) {
    asm volatile("mma.sync.aligned.m16n8k8.row.col.f32.bf16.bf16.f32 {%0,%1,%2,%3}, {%4,%5}, {%6}, {%7,%7,%7,%7};"
        : "=f"(d[0]), "=f"(d[1]), "=f"(d[2]), "=f"(d[3]) : "r"(a0), "r"(a1), "r"(b0), "f"(0.f));
}
DEVI void mma1688c(float (&d)[4], uint32_t a0, uint32_t a1, uint32_t b0, const float (&c)[4]) {
    asm volatile("mma.sync.aligned.m16n8k8.row.col.f32.bf16.bf16.f32 {%0,%1,%2,%3}, {%4,%5}, {%6}, {%7,%8,%9,%10};"
        : "=f"(d[0]), "=f"(d[1]), "=f"(d[2]), "=f"(d[3]) : "r"(a0), "r"(a1), "r"(b0), "f"(c[0]), "f"(c[1]), "f"(c[2]), "f"(c[3]));
}
DEVI uint32_t pack2(float lo, float hi) { uint32_t r; asm("cvt.rn.bf16x2.f32 %0, %1, %2;" : "=r"(r) : "f"(hi), "f"(lo)); return r; }
DEVI uint32_t fbits(float x) { return __float_as_uint(x); }
DEVI float bf_lo(uint32_t x) { return __uint_as_float(x << 16); }
DEVI float bf_hi(uint32_t x) { return __uint_as_float(x & 0xffff0000u); }
DEVI float ex2(float x) { float y; asm("ex2.approx.ftz.f32 %0, %1;" : "=f"(y) : "f"(x)); return y; }
DEVI float rcp(float x) { float y; asm("rcp.approx.ftz.f32 %0, %1;" : "=f"(y) : "f"(x)); return y; }
DEVI void wg_fence() { asm volatile("wgmma.fence.sync.aligned;" ::: "memory"); }
DEVI void wg_commit() { asm volatile("wgmma.commit_group.sync.aligned;" ::: "memory"); }
template <int N> DEVI void wg_wait() { asm volatile("wgmma.wait_group.sync.aligned %0;" :: "n"(N) : "memory"); }
DEVI void wgmma_n32_rs(float (&d)[16], const uint32_t (&a)[4], uint32_t dlo, int sc) {
    asm volatile("{.reg .pred p; .reg .b64 db; mov.b64 db, {%20, 0x40000040}; setp.ne.b32 p, %21, 0; wgmma.mma_async.sync.aligned.m64n32k16.f32.bf16.bf16 {%0,%1,%2,%3,%4,%5,%6,%7,%8,%9,%10,%11,%12,%13,%14,%15}, {%16,%17,%18,%19}, db, p, 1, 1, 0;}"
        : "+f"(d[0]), "+f"(d[1]), "+f"(d[2]), "+f"(d[3]), "+f"(d[4]), "+f"(d[5]), "+f"(d[6]), "+f"(d[7]),
          "+f"(d[8]), "+f"(d[9]), "+f"(d[10]), "+f"(d[11]), "+f"(d[12]), "+f"(d[13]), "+f"(d[14]), "+f"(d[15])
        : "r"(a[0]), "r"(a[1]), "r"(a[2]), "r"(a[3]), "r"(dlo), "r"(sc));
}
DEVI void wgmma_n64_rs(float (&d)[32], const uint32_t (&a)[4], uint64_t db, int sc) {
    asm volatile("{.reg .pred p; setp.ne.b32 p, %37, 0; wgmma.mma_async.sync.aligned.m64n64k16.f32.bf16.bf16 "
        "{%0,%1,%2,%3,%4,%5,%6,%7,%8,%9,%10,%11,%12,%13,%14,%15,%16,%17,%18,%19,%20,%21,%22,%23,%24,%25,%26,%27,%28,%29,%30,%31}, "
        "{%32,%33,%34,%35}, %36, p, 1, 1, 0;}"
        : "+f"(d[0]), "+f"(d[1]), "+f"(d[2]), "+f"(d[3]), "+f"(d[4]), "+f"(d[5]), "+f"(d[6]), "+f"(d[7]),
          "+f"(d[8]), "+f"(d[9]), "+f"(d[10]), "+f"(d[11]), "+f"(d[12]), "+f"(d[13]), "+f"(d[14]), "+f"(d[15]),
          "+f"(d[16]), "+f"(d[17]), "+f"(d[18]), "+f"(d[19]), "+f"(d[20]), "+f"(d[21]), "+f"(d[22]), "+f"(d[23]),
          "+f"(d[24]), "+f"(d[25]), "+f"(d[26]), "+f"(d[27]), "+f"(d[28]), "+f"(d[29]), "+f"(d[30]), "+f"(d[31])
        : "r"(a[0]), "r"(a[1]), "r"(a[2]), "r"(a[3]), "l"(db), "r"(sc));
}
DEVI void wgmma_n64_st(float (&d)[32], uint64_t da, uint64_t db, int sc) {
    asm volatile("{.reg .pred p; setp.ne.b32 p, %34, 0; wgmma.mma_async.sync.aligned.m64n64k16.f32.bf16.bf16 "
        "{%0,%1,%2,%3,%4,%5,%6,%7,%8,%9,%10,%11,%12,%13,%14,%15,%16,%17,%18,%19,%20,%21,%22,%23,%24,%25,%26,%27,%28,%29,%30,%31}, %32, %33, p, 1, 1, 1, 0;}"
        : "+f"(d[0]), "+f"(d[1]), "+f"(d[2]), "+f"(d[3]), "+f"(d[4]), "+f"(d[5]), "+f"(d[6]), "+f"(d[7]), "+f"(d[8]), "+f"(d[9]), "+f"(d[10]), "+f"(d[11]), "+f"(d[12]), "+f"(d[13]), "+f"(d[14]), "+f"(d[15]), "+f"(d[16]), "+f"(d[17]), "+f"(d[18]), "+f"(d[19]), "+f"(d[20]), "+f"(d[21]), "+f"(d[22]), "+f"(d[23]), "+f"(d[24]), "+f"(d[25]), "+f"(d[26]), "+f"(d[27]), "+f"(d[28]), "+f"(d[29]), "+f"(d[30]), "+f"(d[31])
        : "l"(da), "l"(db), "r"(sc));
}
DEVI void wgmma_n128_rs(float (&d)[64], const uint32_t (&a)[4], uint64_t db, int sc) {
    asm volatile("{.reg .pred p; setp.ne.b32 p, %69, 0; wgmma.mma_async.sync.aligned.m64n128k16.f32.bf16.bf16 "
        "{%0,%1,%2,%3,%4,%5,%6,%7,%8,%9,%10,%11,%12,%13,%14,%15,%16,%17,%18,%19,%20,%21,%22,%23,%24,%25,%26,%27,%28,%29,%30,%31,%32,%33,%34,%35,%36,%37,%38,%39,%40,%41,%42,%43,%44,%45,%46,%47,%48,%49,%50,%51,%52,%53,%54,%55,%56,%57,%58,%59,%60,%61,%62,%63}, {%64,%65,%66,%67}, %68, p, 1, 1, 1;}"
        : "+f"(d[0]), "+f"(d[1]), "+f"(d[2]), "+f"(d[3]), "+f"(d[4]), "+f"(d[5]), "+f"(d[6]), "+f"(d[7]), "+f"(d[8]), "+f"(d[9]), "+f"(d[10]), "+f"(d[11]), "+f"(d[12]), "+f"(d[13]), "+f"(d[14]), "+f"(d[15]), "+f"(d[16]), "+f"(d[17]), "+f"(d[18]), "+f"(d[19]), "+f"(d[20]), "+f"(d[21]), "+f"(d[22]), "+f"(d[23]), "+f"(d[24]), "+f"(d[25]), "+f"(d[26]), "+f"(d[27]), "+f"(d[28]), "+f"(d[29]), "+f"(d[30]), "+f"(d[31]), "+f"(d[32]), "+f"(d[33]), "+f"(d[34]), "+f"(d[35]), "+f"(d[36]), "+f"(d[37]), "+f"(d[38]), "+f"(d[39]), "+f"(d[40]), "+f"(d[41]), "+f"(d[42]), "+f"(d[43]), "+f"(d[44]), "+f"(d[45]), "+f"(d[46]), "+f"(d[47]), "+f"(d[48]), "+f"(d[49]), "+f"(d[50]), "+f"(d[51]), "+f"(d[52]), "+f"(d[53]), "+f"(d[54]), "+f"(d[55]), "+f"(d[56]), "+f"(d[57]), "+f"(d[58]), "+f"(d[59]), "+f"(d[60]), "+f"(d[61]), "+f"(d[62]), "+f"(d[63])
        : "r"(a[0]), "r"(a[1]), "r"(a[2]), "r"(a[3]), "l"(db), "r"(sc));
}
DEVI void wgmma_n128_ss(float (&d)[64], uint64_t da, uint64_t db, int sc) {
    asm volatile("{.reg .pred p; setp.ne.b32 p, %66, 0; wgmma.mma_async.sync.aligned.m64n128k16.f32.bf16.bf16 "
        "{%0,%1,%2,%3,%4,%5,%6,%7,%8,%9,%10,%11,%12,%13,%14,%15,%16,%17,%18,%19,%20,%21,%22,%23,%24,%25,%26,%27,%28,%29,%30,%31,"
        "%32,%33,%34,%35,%36,%37,%38,%39,%40,%41,%42,%43,%44,%45,%46,%47,%48,%49,%50,%51,%52,%53,%54,%55,%56,%57,%58,%59,%60,%61,%62,%63}, "
        "%64, %65, p, 1, 1, 0, 1;}"
        : "+f"(d[0]), "+f"(d[1]), "+f"(d[2]), "+f"(d[3]), "+f"(d[4]), "+f"(d[5]), "+f"(d[6]), "+f"(d[7]),
          "+f"(d[8]), "+f"(d[9]), "+f"(d[10]), "+f"(d[11]), "+f"(d[12]), "+f"(d[13]), "+f"(d[14]), "+f"(d[15]),
          "+f"(d[16]), "+f"(d[17]), "+f"(d[18]), "+f"(d[19]), "+f"(d[20]), "+f"(d[21]), "+f"(d[22]), "+f"(d[23]),
          "+f"(d[24]), "+f"(d[25]), "+f"(d[26]), "+f"(d[27]), "+f"(d[28]), "+f"(d[29]), "+f"(d[30]), "+f"(d[31]),
          "+f"(d[32]), "+f"(d[33]), "+f"(d[34]), "+f"(d[35]), "+f"(d[36]), "+f"(d[37]), "+f"(d[38]), "+f"(d[39]),
          "+f"(d[40]), "+f"(d[41]), "+f"(d[42]), "+f"(d[43]), "+f"(d[44]), "+f"(d[45]), "+f"(d[46]), "+f"(d[47]),
          "+f"(d[48]), "+f"(d[49]), "+f"(d[50]), "+f"(d[51]), "+f"(d[52]), "+f"(d[53]), "+f"(d[54]), "+f"(d[55]),
          "+f"(d[56]), "+f"(d[57]), "+f"(d[58]), "+f"(d[59]), "+f"(d[60]), "+f"(d[61]), "+f"(d[62]), "+f"(d[63])
        : "l"(da), "l"(db), "r"(sc));
}
DEVI uint64_t mkdesc(uint32_t addr, uint32_t lbo, uint32_t sbo, uint32_t sw) {
    return (uint64_t)(((addr & 0x3FFFF) >> 4) | ((lbo >> 4) << 16)) | ((uint64_t)((sbo >> 4) | (sw << 30)) << 32);
}
DEVI void bulk_g2s(uint32_t dst, const void* src, uint32_t bytes, uint32_t mb) {
    asm volatile("cp.async.bulk.shared::cluster.global.mbarrier::complete_tx::bytes [%0], [%1], %2, [%3];" :: "r"(dst), "l"(src), "r"(bytes), "r"(mb) : "memory");
}
DEVI void fence_async_global() { asm volatile("fence.proxy.async.global;" ::: "memory"); }
DEVI void red_release(void* a, uint32_t v) { asm volatile("red.release.gpu.global.add.u32 [%0], %1;" :: "l"(a), "r"(v) : "memory"); }
DEVI void tma2d(uint32_t dst, const CUtensorMap* tm, int c0, int c1, uint32_t mb) {
    asm volatile("cp.async.bulk.tensor.2d.shared::cluster.global.mbarrier::complete_tx::bytes [%0], [%1, {%3, %4}], [%2];"
        :: "r"(dst), "l"(tm), "r"(mb), "r"(c0), "r"(c1) : "memory");
}
DEVI void tma3d(uint32_t dst, const CUtensorMap* tm, int c0, int c1, int c2, uint32_t mb) {
    asm volatile("cp.async.bulk.tensor.3d.shared::cluster.global.mbarrier::complete_tx::bytes [%0], [%1, {%3, %4, %5}], [%2];"
        :: "r"(dst), "l"(tm), "r"(mb), "r"(c0), "r"(c1), "r"(c2) : "memory");
}
DEVI void tma2d_mc(uint32_t dst, const CUtensorMap* tm, int c0, int c1, uint32_t mb, uint16_t mask) {
    asm volatile("cp.async.bulk.tensor.2d.shared::cluster.global.mbarrier::complete_tx::bytes.multicast::cluster [%0], [%1, {%3, %4}], [%2], %5;"
        :: "r"(dst), "l"(tm), "r"(mb), "r"(c0), "r"(c1), "h"(mask) : "memory");
}
DEVI void bulk_g2s_mc(uint32_t dst, const void* src, uint32_t bytes, uint32_t mb, uint16_t mask) {
    asm volatile("cp.async.bulk.shared::cluster.global.mbarrier::complete_tx::bytes.multicast::cluster [%0], [%1], %2, [%3], %4;"
        :: "r"(dst), "l"(src), "r"(bytes), "r"(mb), "h"(mask) : "memory");
}
DEVI void mbar_arrive_cnt(uint32_t a, uint32_t n) { asm volatile("mbarrier.arrive.relaxed.cluster.shared::cluster.b64 _, [%0], %1;" :: "r"(a), "r"(n) : "memory"); }
DEVI bool elect() { uint32_t p; asm volatile("{.reg .pred p; elect.sync _|p, 0xffffffff; selp.u32 %0, 1, 0, p;}" : "=r"(p)); return p; }
DEVI void tma2d_prefetch(const CUtensorMap* tm, int c0, int c1) {
    asm volatile("cp.async.bulk.prefetch.tensor.2d.L2.global [%0, {%1, %2}];" :: "l"(tm), "r"(c0), "r"(c1) : "memory");
}
DEVI void bulk_prefetch(const void* p, uint32_t bytes) { asm volatile("cp.async.bulk.prefetch.L2.global [%0], %1;" :: "l"(p), "r"(bytes) : "memory"); }
DEVI void bulk_s2g(void* dst, uint32_t src, uint32_t bytes) {
    asm volatile("cp.async.bulk.global.shared::cta.bulk_group [%0], [%1], %2;" :: "l"(dst), "r"(src), "r"(bytes) : "memory");
}
DEVI void bulk_s2s(uint32_t dst, uint32_t src, uint32_t bytes, uint32_t mb) {
    asm volatile("cp.async.bulk.shared::cluster.shared::cta.mbarrier::complete_tx::bytes [%0], [%1], %2, [%3];" :: "r"(dst), "r"(src), "r"(bytes), "r"(mb) : "memory");
}
DEVI void bulk_commit() { asm volatile("cp.async.bulk.commit_group;" ::: "memory"); }
template <int N> DEVI void bulk_wait() { asm volatile("cp.async.bulk.wait_group %0;" :: "n"(N) : "memory"); }
template <int N> DEVI void bulk_wait_read() { asm volatile("cp.async.bulk.wait_group.read %0;" :: "n"(N) : "memory"); }
DEVI uint2 ld_relaxed2(const void* a) { uint2 v; asm volatile("ld.relaxed.gpu.global.v2.b32 {%0,%1}, [%2];" : "=r"(v.x), "=r"(v.y) : "l"(a) : "memory"); return v; }
DEVI void st_relaxed2(void* a, uint32_t x, uint32_t y) { asm volatile("st.relaxed.gpu.global.v2.b32 [%0], {%1,%2};" :: "l"(a), "r"(x), "r"(y) : "memory"); }
DEVI void st_release(void* a, uint32_t v) { asm volatile("st.release.gpu.global.b32 [%0], %1;" :: "l"(a), "r"(v) : "memory"); }
DEVI void st_relaxed(void* a, uint32_t v) { asm volatile("st.relaxed.gpu.global.b32 [%0], %1;" :: "l"(a), "r"(v) : "memory"); }
#define ST_FLAG st_relaxed
DEVI uint32_t ld_acquire(const void* a) { uint32_t v; asm volatile("ld.acquire.gpu.global.b32 %0, [%1];" : "=r"(v) : "l"(a) : "memory"); return v; }
DEVI uint32_t ld_relaxed(const void* a) { uint32_t v; asm volatile("ld.relaxed.gpu.global.b32 %0, [%1];" : "=r"(v) : "l"(a) : "memory"); return v; }
template <int N> DEVI void reg_inc() { asm volatile("setmaxnreg.inc.sync.aligned.u32 %0;" :: "n"(N)); }
template <int N> DEVI void reg_dec() { asm volatile("setmaxnreg.dec.sync.aligned.u32 %0;" :: "n"(N)); }

constexpr int KV_BYTES = 16384;
__device__ __align__(1024) unsigned char gKV[(size_t)NSEG * 32 * KV_BYTES];
__device__ __align__(1024) uint4 gM[NSEG * 32 * 512];
constexpr int VB_SEG = 60;
#define KRS 2
constexpr int KR_SEG = KRS;
__device__ __align__(65536) unsigned char gX[16 * 65536];
__device__ uint32_t gFlagKV[64 * 32];
__device__ __align__(1024) unsigned char gH[16 * 22 * 16384];
__device__ __align__(1024) unsigned char gO[32 * 32 * 16384];
__device__ __align__(1024) unsigned char gP[32 * 4 * 9 * 16384];
__device__ __align__(1024) uint4 gPL[4 * 8 * 2048];
__device__ uint32_t gDone;
__device__ __align__(128) uint32_t gFlagK[32 * 32];
__device__ uint32_t gCntH[16 * 32], gFlagO[32 * 32], gCntP[128 * 32];
#define DBG0
#define DBG1(k)
#define TLS(row, i)
#define TPS(i)
#define PROBE_DECL
#define PROBE(i)
#define STAMP(i)

namespace R {
constexpr uint32_t WO = 0, XB = 65536, STG = 131072, KVB = STG + 40960, MEMB = 196608, QP = 204800, OB = 206848,
                   SCO = 207872, SCR = 209152, RS = 210432, MB = 218624, PROFB = MB + 320,
                   SMEM_BYTES = MB + 320;
constexpr uint32_t B_W1K = MB, B_W1V = MB + 8, B_W2Q = MB + 16, B_W2O = MB + 24, B_X = MB + 32  , B_AG = MB + 48  ,
                   B_SC = MB + 112, B_RS = MB + 120  , B_KX = MB + 136  , B_VM = MB + 152  , EPOCH = MB + 192, KMODE = MB + 208  , KFLG = MB + 224  , DIST = MB + 288  ;
constexpr int BAR_A = 1, BAR_B = 2, BAR_C = 3, BAR_D = 4, BAR_F = 5, BAR_G = 7, BAR_W = 8, BAR_E = 9, BAR_V = 10  ;
#define AGM 0x5125
constexpr uint64_t ag_table(bool sizes) {
    uint64_t t = 0; int g = -1;
    for (int i = 0; i < 16; i++) { g += (AGM >> i) & 1; t += sizes ? 1ull << (4 * g) : (uint64_t)g << (4 * i); }
    return t;
}
constexpr uint64_t AG_GROUPS = ag_table(false), AG_SIZES = ag_table(true);
__host__ __device__ constexpr int ag_group(int slot) { return (AG_GROUPS >> (4 * slot)) & 15; }
__host__ __device__ constexpr int ag_size(int g) { return (AG_SIZES >> (4 * g)) & 15; }
constexpr int NAG = ag_group(15) + 1;
#define NXW 32
#define RG0 224
#define RG1 224
#define RG2 56
#define NPF0 8
#define NPF1 4
#define WOBAR 0
#define XPOS 0
#ifndef NVS
#define NVS 1
#endif
#define VGATE 1
#define NB10 12
#define NB11 8
#define PDELAY 180
#define HOME 1
#define NX1 0
#define QD0 5
#define QD1 2
#define QF0 0
#define QF1 0
#define VDEP 1
#define XD16 1
#define MSUM 2
#define AGV 1
#define PUB2 1
#define PUBPOS 1
#define NPROBE 4
#define PSTAG 20
#define NSW0 8
#define NSW1 8
#define RCH 2
#define CH1 1
#define NKA 3
#define VODD 1
#define VPIN 0
constexpr int REG0 = RG0, REG1 = RG1, REG2 = RG2;

template <int G>
DEVI void compute_wg(const uint32_t sb, const uint32_t rank, const int head, const int wi, const int lane, const CUtensorMap* tm2) {
    constexpr int wg = G;
    constexpr int NPF = G == 0 ? NPF0 : NPF1, NB1 = G == 0 ? NB10 : NB11, NSW = G == 0 ? NSW0 : NSW1;
    PROBE_DECL
    const uint32_t half = rank & 1;
    uint32_t wkv[32][4];
    uint32_t wq[16][4];
    uint32_t wlane = opaque(sb + ((lane >> 4) * 8 + (lane & 7)) * 128 + (((wi * 2 + ((lane >> 3) & 1)) ^ (lane & 7)) << 4));
    if (wi == 0 && lane == 0 && G == 0) TPS(1);
    mbar_wait(sb + (G == 0 ? B_W1K : B_W1V), 0);
    if (wi == 0 && lane == 0) TPS(2 + G);
#pragma unroll
    for (int i = 0; i < 32; i++) ldsm4t(wkv[i], wlane + (G == 0 ? WO : STG) + i * 2048);
    fence_async_smem();
    bar_sync(BAR_W + G * 6, 128);
    if (G == 0) { if (lane < 2) tma2d(sb + WO + (wi * 2 + lane) * 8192, tm2, (wi * 2 + lane) * 64, head * 128 + half * 64, sb + B_W2O); }
    else if (lane < 4) tma2d(sb + STG + (wi * 4 + lane) * 2048, tm2, head * 128 + half * 64, ((rank + wi * 4 + lane) & 15) * 32, sb + B_W2Q);
    __syncwarp();
    auto load_wq = [&](int i0, int i1) {
#pragma unroll
        for (int i = 0; i < 16; i++) if (i >= i0 && i < i1) ldsm4t(wq[i], wlane + (i < 8 ? STG : XB + 32768) + ((((i >> 1) * 2 + G) & 7) * 2 + (i & 1)) * 2048);
    };
    const uint32_t slA = (rank + G * 4 + wi) & 15;
    const uint32_t wo_x = ((wi * 2) ^ ((slA & 1) * 4)) << 4;
    const uint32_t wo_a = WO + (slA >> 1) * 8192, wo_b = WO + ((slA ^ 8) >> 1) * 8192;
    const uint32_t rs_a = (mapa(sb, slA) - (sb >> 1)) + RS + (G * 4 + wi) * 256, rs_b = (mapa(sb, slA ^ 8) - (sb >> 1)) + RS + 2048 + (G * 4 + wi) * 256;
    const uint32_t rsb_a = mapa(sb + B_RS, slA), rsb_b = mapa(sb + B_RS, slA ^ 8);
    uint32_t l16 = opaque(sb + lane * 16);
    const uint32_t lm = opaque(sb + MEMB + (lane >> 4) * 256 + ((lane >> 2) & 1) * 128 + ((lane & 3) + 4 * (((lane >> 3) ^ (lane >> 2)) & 1)) * 16);
    uint32_t r128 = rank * 128;
    uint32_t xoff[16];
#pragma unroll
    for (int i = 0; i < 16; i++) { xoff[i] = (r128 + i * 128) & 0x700; if (XD16 && G == 1) pin(xoff[i]); }
    bool kmode = true;
    auto send_m = [&](int j, uint32_t w0, uint32_t w1) {
        st_tagged((unsigned char*)gM + ((size_t)(j * 32 + head) * 8192 + G * 4096 + half * 2048 + wi * 512) + (l16 - sb), w0, w1, lds1(sb + EPOCH) + 1);
    };

    auto project_x = [&](const int j, const bool gated) {
        const uint32_t ph = j & 1, kvb = KVB + ph * 10240 + G * 5120;
        { DBG0 mbar_wait(sb + B_X + ph * 8, (j >> 1) & 1); if (wi == 0) DBG1(0); }
        float acc[16];
        {
            const uint32_t xe = ((((sb + XB) >> 4) & 0x3fff) | (1u << 16)) + ph * 2048 + half * 4, xo = xe ^ 4;
            pin(r128);
            wg_fence();
#pragma unroll
            for (int i = 0; i < NXW; i++) {
                if (gated && i == NX1) bar_sync(BAR_E, 384);
                if (XD16 && G == 1) wgmma_n32_rs(acc, wkv[i], xoff[i >> 1] + ((i & 2) ? xo : xe) + (i & 1) * 2, i > 0);
                else wgmma_n32_rs(acc, wkv[i], ((r128 + (i >> 1) * 128) & 0x700) + ((i & 2) ? xo : xe) + (i & 1) * 2, i > 0);
            }
            wg_commit();
        }
        wg_wait<0>();
        PROBE(1);
        {
            const uint32_t dst = l16 + kvb + wi * 1024;
            stsm4(dst, pack2(acc[0], acc[1]), pack2(acc[4], acc[5]), pack2(acc[8], acc[9]), pack2(acc[12], acc[13]));
            stsm4(dst + 512, pack2(acc[2], acc[3]), pack2(acc[6], acc[7]), pack2(acc[10], acc[11]), pack2(acc[14], acc[15]));
        }
    };
    bar_sync(BAR_F, 256);
    project_x(0, false);
    mbar_wait(sb + B_W2Q, 0);
    if (wi == 0 && lane == 0 && G == 0) TPS(4);
    load_wq(NSW, 16);
    fence_async_smem();
    cluster_arrive_relaxed();

#pragma unroll 1
    for (int j = 0; j < NSEG; j++) {
        const uint32_t ph = j & 1;
        const uint32_t kvb = KVB + ph * 10240 + G * 5120;
        pin(l16); pin(wlane);
        PROBE(0);
#pragma unroll
        for (int i = 0; i < NSW; i++) { load_wq(i, i + 1); if (i % RCH == RCH - 1) wlane |= wq[i][0] & (l16 & 8); }
        if (G == 0 ? kmode : j == 0 || j == NSEG - 1) {
            bar_arrive(BAR_E, 384);
            if (HOME && G == 0 && j >= 1 && j <= NPROBE && wi < 2) {
                uint32_t v = 0;
                const uint32_t c0 = clock_lo();
                if (l16 == sb) v = atomicAdd((uint32_t*)(gX + rank * 65536 + 32768 + wi * 4096 + (head >> 3) * 128), 1);
                v = __shfl_sync(0xffffffffu, v, 0);
                const uint32_t dt = clock_lo() + (v >> 31) - c0;
                if (l16 == sb) sts1(sb + DIST + wi * 4, min(dt, lds1(sb + DIST + wi * 4)));
                __syncwarp();
            }
        } else {
            project_x(j, true);
        }
        bar_arrive(BAR_C, 384);
        PROBE(2);
        uint32_t wo[16][4];
        auto load_wo = [&](int i) { ldsm4t(wo[i], (wlane ^ wo_x ^ ((i >> 3) * 32)) + (i & 1 ? wo_b : wo_a) + ((i >> 1) & 3) * 2048); };
        auto kv = [&](int n, int e) -> const uint32_t (&)[4] { return wkv[((n & 7) * 2 + e) * 2 + (n >> 3)]; };
        auto chain = [&](uint32_t& addr, uint32_t v) { addr |= v & (l16 & 8); };
        if (G == 0) {
            uint32_t k0, k1;
            for (int tries = 0;; tries++) {
                float ak[NKA][4], aq[2][4];
                uint32_t b[16][4];
                uint32_t ma = lm;
#pragma unroll
                for (int i = 0; i < 16; i++) {
                    if ((AGM >> i) & 1) {
                        if ((QF0 >> i) & 1) sched_fence(l16);
                        ma = mbar_try_addr(sb + B_AG + ag_group(i) * 8, ph, ma, sb);
#pragma unroll
                        for (int u = 0; u < 16; u++) if (ag_group(u) == ag_group(i)) ldsm4t(b[u], ma + u * 512);
                    }
                    if (i == 0) { mma16816z(aq[0], wq[0], b[0][0], b[0][1]); mma16816z(aq[1], wq[1], b[0][2], b[0][3]); }
                    if (2 * i < NKA) mma16816z(ak[2 * i], kv(i, 0), b[i][0], b[i][1]); else mma16816(ak[(2 * i) % NKA], kv(i, 0), b[i][0], b[i][1]);
                    if (2 * i + 1 < NKA) mma16816z(ak[2 * i + 1], kv(i, 1), b[i][2], b[i][3]); else mma16816(ak[(2 * i + 1) % NKA], kv(i, 1), b[i][2], b[i][3]);
                    if (i > 0 && !(i & 1)) { mma16816(aq[0], wq[i], b[i][0], b[i][1]); mma16816(aq[1], wq[i + 1], b[i][2], b[i][3]); }
                    if ((QD0 >> i) & 1) chain(ma, fbits(aq[0][0]) | fbits(aq[1][0]) | fbits(ak[0][0]) | fbits(ak[1][0]) | (i > 0 ? fbits(ak[NKA - 1][0]) : 0u));
                }
                stsm2(l16 + QP + wi * 256, pack2(aq[0][0] + aq[1][0], aq[0][1] + aq[1][1]), pack2(aq[0][2] + aq[1][2], aq[0][3] + aq[1][3]));
                float kk[4];
#pragma unroll
                for (int i = 0; i < 4; i++) kk[i] = NKA == 4 ? (ak[0][i] + ak[1][i]) + (ak[NKA - 2][i] + ak[NKA - 1][i]) : NKA == 3 ? (ak[NKA - 1][i] + ak[0][i]) + ak[1][i] : ak[0][i] + ak[1][i];
                k0 = pack2(kk[0], kk[1]); k1 = pack2(kk[2], kk[3]);
                stsm2(l16 + kvb + 4096 + wi * 256, k0, k1);
                bar_arrive_if_eq(BAR_A, 384, ma, lm);
                if (__all_sync(0xffffffffu, ma == lm)) break;
                if (tries > (1 << 18)) { fault_if(true); break; }
                load_wq(0, NSW);
            }
            PROBE(3);
            if (j == NSEG - 1) { send_m(j, k0, k1); break; }
            if (j == 0) { cluster_wait(); mbar_wait(sb + B_W2O, 0); }
            bar_sync(BAR_D, 384);
            send_m(j, k0, k1);
            kmode = __any_sync(0xffffffffu, lds1(sb + KMODE + (ph ^ 1) * 4) != 0);
#pragma unroll
            for (int i = 0; i < NPF; i++) { load_wo(i); chain(wlane, wo[i][0]); }
        } else {
            uint32_t b[16][4];
            float av[4][4];
            for (int tries = 0;; tries++) {
                float aq[2][4];
                uint32_t ma = lm;
#pragma unroll
                for (int i = 0; i < 16; i++) {
                    if ((AGM >> i) & 1) {
                        if ((QF1 >> i) & 1) sched_fence(l16);
                        ma = mbar_try_addr(sb + B_AG + ag_group(i) * 8, ph, ma, sb);
#pragma unroll
                        for (int u = 1; u < 16; u += 2) if (ag_group(u) == ag_group(i)) ldsm4t(b[u], ma + u * 512);
                    }
                    if (!(i & 1)) continue;
                    if (i == 1) {
                        mma16816z(aq[0], wq[0], b[1][0], b[1][1]); mma16816z(aq[1], wq[1], b[1][2], b[1][3]);
                        mma16816z(av[0], kv(1, 0), b[1][0], b[1][1]); mma16816z(av[1], kv(1, 1), b[1][2], b[1][3]);
                    } else {
                        mma16816(aq[0], wq[i - 1], b[i][0], b[i][1]); mma16816(aq[1], wq[i], b[i][2], b[i][3]);
                        if (i < NVS) { mma16816(av[0], kv(i, 0), b[i][0], b[i][1]); mma16816(av[1], kv(i, 1), b[i][2], b[i][3]); }
                    }
                    if ((QD1 >> i) & 1) chain(ma, fbits(aq[0][0]) | fbits(aq[1][0]) | fbits(av[0][0]) | fbits(av[1][0]));
                }
                stsm2(l16 + QP + 1024 + wi * 256, pack2(aq[0][0] + aq[1][0], aq[0][1] + aq[1][1]), pack2(aq[0][2] + aq[1][2], aq[0][3] + aq[1][3]));
                bar_arrive_if_eq(BAR_A, 384, ma, lm);
                if (__all_sync(0xffffffffu, ma == lm)) break;
                if (tries > (1 << 18)) { fault_if(true); break; }
                load_wq(0, NSW);
            }
            PROBE(3);
            if (j == 0) cluster_wait();
            if (j < NSEG - 1) { bar_sync(BAR_D, 384); sched_fence(l16); }
            {
                int n = 0;
#pragma unroll
                for (int pass = 0; pass < 2; pass++)
#pragma unroll
                    for (int i = 0; i < 16; i++) {
                        const bool late = !(i & 1);
                        if (pass == 0 ? (late || i < NVS || i == 1) : !late) continue;
                        if (late) ldsm4t(b[i], lm + i * 512);
                        if (n == 0) { mma16816z(av[2], kv(i, 0), b[i][0], b[i][1]); mma16816z(av[3], kv(i, 1), b[i][2], b[i][3]); }
                        else { mma16816(av[((n + 1) & 1) * 2], kv(i, 0), b[i][0], b[i][1]); mma16816(av[((n + 1) & 1) * 2 + 1], kv(i, 1), b[i][2], b[i][3]); }
                        n++;
                    }
            }
            const uint32_t v0 = pack2((av[0][0] + av[1][0]) + (av[2][0] + av[3][0]), (av[0][1] + av[1][1]) + (av[2][1] + av[3][1]));
            const uint32_t v1 = pack2((av[0][2] + av[1][2]) + (av[2][2] + av[3][2]), (av[0][3] + av[1][3]) + (av[2][3] + av[3][3]));
            if (j == NSEG - 1) {
                send_m(j, v0, v1);
                break;
            }
            stsm2(l16 + kvb + 4096 + wi * 256, v0, v1);
            __syncwarp();
            if (l16 == sb) mbar_arrive(sb + B_VM + wi * 8);
            send_m(j, v0, v1);
            PROBE(4);
#pragma unroll
            for (int i = 0; i < NPF; i++) { load_wo(i); if (i % CH1 == CH1 - 1) chain(wlane, wo[i][0]); }
        }
        PROBE(5);
        bar_sync(BAR_B, 384);
        {
            uint32_t b[2][4];
            ldsm4t(b[0], l16 + OB);
            ldsm4t(b[1], l16 + OB + 512);
            wlane |= b[0][0] & (l16 & 8);
#pragma unroll
            for (int i = NPF; i < 8; i++) load_wo(i);
            float a0[4], a1[4], a2[4], a3[4];
            mma16816z(a0, wo[0], b[0][0], b[0][1]); mma16816z(a1, wo[1], b[0][0], b[0][1]);
            mma16816z(a2, wo[2], b[0][2], b[0][3]); mma16816z(a3, wo[3], b[0][2], b[0][3]);
#pragma unroll
            for (int i = 8; i < NB1; i++) if (i >= NPF) load_wo(i);
            mma16816(a0, wo[4], b[1][0], b[1][1]); mma16816(a1, wo[5], b[1][0], b[1][1]);
            mma16816(a2, wo[6], b[1][2], b[1][3]); mma16816(a3, wo[7], b[1][2], b[1][3]);
            st_async2((l16 >> 1) + rs_a, rsb_a, pack2(a0[0] + a2[0], a0[1] + a2[1]), pack2(a0[2] + a2[2], a0[3] + a2[3]));
            st_async2((l16 >> 1) + rs_b, rsb_b, pack2(a1[0] + a3[0], a1[1] + a3[1]), pack2(a1[2] + a3[2], a1[3] + a3[3]));
            sched_fence(l16);
#pragma unroll
            for (int i = NB1; i < 16; i++) load_wo(i);
            mma16816z(a0, wo[8], b[0][0], b[0][1]); mma16816z(a1, wo[9], b[0][0], b[0][1]);
            mma16816z(a2, wo[10], b[0][2], b[0][3]); mma16816z(a3, wo[11], b[0][2], b[0][3]);
            mma16816(a0, wo[12], b[1][0], b[1][1]); mma16816(a1, wo[13], b[1][0], b[1][1]);
            mma16816(a2, wo[14], b[1][2], b[1][3]); mma16816(a3, wo[15], b[1][2], b[1][3]);
            st_async2((l16 >> 1) + rs_a + 4096, rsb_a + 8, pack2(a0[0] + a2[0], a0[1] + a2[1]), pack2(a0[2] + a2[2], a0[3] + a2[3]));
            st_async2((l16 >> 1) + rs_b + 4096, rsb_b + 8, pack2(a1[0] + a3[0], a1[1] + a3[1]), pack2(a1[2] + a3[2], a1[3] + a3[3]));
        }
        PROBE(7);
        if (WOBAR) bar_sync(BAR_F, 256);
    }
    cluster_arrive_relaxed();
    cluster_wait();
}

DEVI void comm_wg(const uint32_t sb, const uint32_t rank, const uint32_t cid, const int head, const int wi, const int lane,
                  const CUtensorMap* tmX, const __nv_bfloat16* mem0) {
    constexpr int wg = 2;
    PROBE_DECL
    const uint32_t half = rank & 1;
    uint32_t word;
    {
        const int c = rank * 32 + (wi >> 1) * 16 + (lane & 1) * 8 + (wi & 1) * 4 + (lane >> 3), t = ((lane >> 1) & 3) * 2;
        const unsigned short* m = (const unsigned short*)mem0;
        word = (uint32_t)m[t * 512 + c] | ((uint32_t)m[(t + 1) * 512 + c] << 16);
    }
    const uint32_t lq = opaque(sb + QP + ((lane >> 3) & 1) * 1024 + (lane >> 4) * 128 + (lane & 7) * 16);
    uint32_t l8 = opaque(sb + lane * 8);
    uint32_t wl4 = opaque(sb + wi * 128 + lane * 4);
    const bool l0 = l8 == sb;
    const float sc2 = 0.08838834764831845f * 1.4426950408889634f;
    auto ag_addr = [&]() {};
    uint32_t da = opaque(sb + MEMB + (wi >> 1) * 4096 + (wi & 1) * 128 + ((lane >> 3) + 4 * ((lane ^ wi) & 1)) * 16 + ((lane >> 1) & 3) * 4);
    uint32_t db = opaque(sb + B_AG + (wi >> 1) * ag_group(8) * 8);
    auto all_gather = [&](uint32_t w) {
        static_assert((AGM & 0x100) != 0, "");
        const bool u = wi >> 1;
#pragma unroll
        for (int n = 0; n < 16; n++) {
            const int i = n < 2 ? 1 - n : n;
            const uint32_t go = (u ? ag_group(8 + (i >> 1)) - ag_group(8) : ag_group(i >> 1)) * 8;
            const uint32_t a = (da + (((16u - i) << 24) + i * 256u)) & 0x0fffffffu, b = (db + (((16u - i) << 24) + go)) & 0x0fffffffu;
            st_async1(a, b, w);
        }
        pin(da); pin(db);
    };
    all_gather(word);
#pragma unroll
    for (int i = 0; i < (HOME ? 4 : 2); i++) st_relaxed64(gX + rank * 65536 + (i & 1) * 16384 + (i >> 1) * 4096 + cid * 1024 + (wl4 - sb) * 2, 0, 0);
    cluster_arrive_relaxed();
    if (NX1 < NXW) bar_arrive(BAR_E, 384);
    cluster_wait();
    int kstate = 0;
    auto fetch_k = [&](int s) {
        const uint32_t bar = sb + B_KX + (s & 1) * 8;
        const unsigned char* src = gKV + ((size_t)s * 32 + head) * KV_BYTES + half * 4096;
        if (kstate == 2) {
            if (elect()) { mbar_expect(bar, 4096); bulk_g2s(sb + KVB + (s & 1) * 10240, src, 4096, bar); }
        } else {
            const uint32_t par = (s >> 1) & 1, need = (s >> 2) + 1;
            mbar_wait(sb + B_KX + ((s & 1) ^ 1) * 8, ((s - 1) >> 1) & 1);
            const uint32_t ep = lds1(sb + EPOCH) * 32;
            uint32_t got = lds1(sb + KFLG + ((s & 1) ^ 1) * 32 + par * 16) - ep, other = lds1(sb + KFLG + ((s & 1) ^ 1) * 32 + (par ^ 1) * 16) - ep;
            bool ok = s >= KR_SEG && kstate >= 0;
            if (ok && __all_sync(0xffffffffu, got == 16 && other == 16)) kstate++;
            if (ok && __any_sync(0xffffffffu, got > 32 || got < need)) {
                const uint32_t c0 = clock_lo();
                do {
                    got = ld_acquire(gFlagK + head * 32 + par * 4) - ep;
                    ok = __all_sync(0xffffffffu, got <= 32 && got >= need);
                } while (!ok && __all_sync(0xffffffffu, clock_lo() - c0 < 100000));
                if (!ok) kstate = -1;
                fence_async_global();
            }
            if (elect()) {
                mbar_expect(bar, ok ? 4128 : 32);
                bulk_g2s(sb + KFLG + (s & 1) * 32, gFlagK + head * 32, 32, bar);
                if (ok) bulk_g2s(sb + KVB + (s & 1) * 10240, src, 4096, bar);
                sts1(sb + KMODE + (s & 1) * 4, ok || s == NSEG - 1);
            }
        }
        __syncwarp();
    };

#pragma unroll 1
    for (int j = 0; j < NSEG; j++) {
        const uint32_t ph = j & 1;
        const uint32_t kvb = KVB + ph * 10240;
        pin(l8); pin(wl4);
        PROBE(1);
        bar_sync(BAR_C, 384);
        auto load_x = [&]() {
            if (elect()) {
                mbar_expect(sb + B_X + (ph ^ 1) * 8, 32768);
                tma2d_mc(sb + XB + (ph ^ 1) * 32768 + rank * 2048, tmX, (rank >> 1) * 64, (j + 1) * 32 + half * 16, sb + B_X + (ph ^ 1) * 8, 0xffff);
                if (j + 4 < NSEG) tma2d_prefetch(tmX, (rank >> 1) * 64, (j + 4) * 32 + half * 16);
            }
            __syncwarp();
        };
        auto publish = [&]() {
            if (j > 0 && j <= VB_SEG) {
                if (PUB2 && ph) bulk_wait_read<0>();
                else { bulk_wait<0>(); if (elect()) ST_FLAG(gFlagKV + (head * 2 + half) * 32, lds1(sb + EPOCH) * 64 + j); }
            }
            __syncwarp();
        };
        if (j == NSEG - 1) { bar_arrive(BAR_A, 384); mbar_wait(sb + B_KX + 8, 1); break; }
        uint32_t vx[2][4];
        {
            const uint32_t o = (l8 - sb) * 2;
            const uint32_t vxa = sb + kvb + 5120 + wi * 1024 + ((o >> 7) & 1) * 512 + (o >> 8) * 128 + (o & 127);
            ldsm4(vx[0], vxa);
            ldsm4(vx[1], vxa + 256);
        }
        uint32_t rb = (sb ^ (1u << 24)) + B_SC;
        uint32_t ra = (l8 ^ (1u << 24)) + SCR + wi * 512;
        if (wi < 2) {
            uint32_t kx[4][4];
            { DBG0 mbar_wait(sb + B_KX + ph * 8, (j >> 1) & 1); if (wi == 0) DBG1(1); }
            {
                const uint32_t o = (l8 - sb) * 2;
                const uint32_t kxa = sb + kvb + (o >> 7) * 512 + wi * 256 + (o & 127);
                ldsm4t(kx[0], kxa); ldsm4t(kx[1], kxa + 2048); ldsm4t(kx[2], kxa + 128); ldsm4t(kx[3], kxa + 2048 + 128);
            }
            pin(ra); pin(rb);
            PROBE(2);
            bar_sync(BAR_A, 384);
            uint32_t q[4][4];
            ldsm4t(q[0], lq); ldsm4t(q[1], lq + 256); ldsm4t(q[2], lq + 512); ldsm4t(q[3], lq + 768);
            float s0[4], s1[4], t0[4], t1[4];
            mma16816z(s0, q[0], kx[0][0], kx[0][1]); mma16816z(t0, q[0], kx[2][0], kx[2][1]);
            mma16816z(s1, q[1], kx[0][2], kx[0][3]); mma16816z(t1, q[1], kx[2][2], kx[2][3]);
            mma16816(s0, q[2], kx[1][0], kx[1][1]); mma16816(t0, q[2], kx[3][0], kx[3][1]);
            mma16816(s1, q[3], kx[1][2], kx[1][3]); mma16816(t1, q[3], kx[3][2], kx[3][3]);
            const uint32_t x = __float_as_uint((s0[0] + s0[2]) + (s1[0] + s1[2])), y = __float_as_uint((s0[1] + s0[3]) + (s1[1] + s1[3]));
            const uint32_t z = __float_as_uint((t0[0] + t0[2]) + (t1[0] + t1[2])), w = __float_as_uint((t0[1] + t0[3]) + (t1[1] + t1[3]));
            st_async2(ra, rb, x, y);
            st_async2(ra + 256, rb, z, w);
            sts2(l8 + SCO + wi * 512, x, y);
            sts2(l8 + SCO + wi * 512 + 256, z, w);
        } else if (wi == 2) {
            if (j == 0) fetch_k(1);
            uint32_t kma = l8 + (l8 - sb) + kvb + 4096;
            pin(ra); pin(rb); pin(kma);
            bar_sync(BAR_A, 384);
            uint32_t q[4][4], km[2][4];
            ldsm4t(km[0], kma); ldsm4t(q[0], lq); ldsm4t(q[1], lq + 256);
            ldsm4t(km[1], kma + 512); ldsm4t(q[2], lq + 512); ldsm4t(q[3], lq + 768);
            float t0[4], t1[4], t2[4], t3[4];
            mma16816z(t0, q[0], km[0][0], km[0][1]);
            mma16816z(t1, q[1], km[0][2], km[0][3]);
            mma16816z(t2, q[2], km[1][0], km[1][1]);
            mma16816z(t3, q[3], km[1][2], km[1][3]);
            const uint32_t z = __float_as_uint(((t0[0] + t0[2]) + (t1[0] + t1[2])) + ((t2[0] + t2[2]) + (t3[0] + t3[2])));
            const uint32_t w = __float_as_uint(((t0[1] + t0[3]) + (t1[1] + t1[3])) + ((t2[1] + t2[3]) + (t3[1] + t3[3])));
            st_async2(ra, rb, z, w);
            sts2(l8 + SCO + 1024, z, w);
        } else {
            bar_arrive(BAR_A, 384);
            DBG0
            if (j + 1 < NSEG - 1) load_x();
            if (PUBPOS == 0 || j == VB_SEG) publish();
            DBG1(3);
        }
        PROBE(4);
        bar_sync(BAR_D, 384);
        float2 s[5];
#pragma unroll
        for (int t = 0; t < 5; t++) s[t] = lds2f(l8 + SCO + t * 256);
        uint32_t one = 0x3f803f80u;
        uint32_t vma = wl4 + wi * 128 + kvb + 5120 + 4096, oa = wl4 + wi * 128 + OB;
        uint32_t vbar = sb + B_VM + wi * 8;
        pin(vma); pin(oa); pin(vbar);
        mbar_wait(sb + B_SC, ph);
        PROBE(5);
        {
            float2 r[5];
#pragma unroll
            for (int t = 0; t < 5; t++) r[t] = lds2f(l8 + SCR + t * 256);
#pragma unroll
            for (int t = 0; t < 5; t++) { s[t].x += r[t].x; s[t].y += r[t].y; }
        }
        float m = fmaxf(fmaxf(fmaxf(s[0].x, s[0].y), fmaxf(s[1].x, s[1].y)), fmaxf(fmaxf(s[2].x, s[2].y), fmaxf(s[3].x, s[3].y)));
        m = fmaxf(m, fmaxf(s[4].x, s[4].y));
        const float mloc = m;
        {
            const float m1 = __shfl_xor_sync(0xffffffffu, m, 1), m2 = __shfl_xor_sync(0xffffffffu, m, 2), m3 = __shfl_xor_sync(0xffffffffu, m, 3);
            m = fmaxf(fmaxf(m, m1), fmaxf(m2, m3));
        }
        const float mb = -m * sc2;
        {
            const uint32_t va = mbar_try_addr(vbar | (fbits(VDEP ? mb : mloc) & (l8 & 4)), ph, vma, sb);
            uint32_t vm0 = lds1(va), vm1 = lds1(va + 128);
            float l[4], l2[4], o0[4], o1[4];
            const uint32_t p0 = pack2(ex2(fmaf(s[0].x, sc2, mb)), ex2(fmaf(s[0].y, sc2, mb)));
            const uint32_t p1 = pack2(ex2(fmaf(s[1].x, sc2, mb)), ex2(fmaf(s[1].y, sc2, mb)));
            mma16816z(l, one, one, one, one, p0, p1);
            mma16816z(o0, vx[0], p0, p1);
            const uint32_t p2 = pack2(ex2(fmaf(s[2].x, sc2, mb)), ex2(fmaf(s[2].y, sc2, mb)));
            const uint32_t p3 = pack2(ex2(fmaf(s[3].x, sc2, mb)), ex2(fmaf(s[3].y, sc2, mb)));
            mma16816(l, one, one, one, one, p2, p3);
            mma16816(o0, vx[1], p2, p3);
            const uint32_t p4 = pack2(ex2(fmaf(s[4].x, sc2, mb)), ex2(fmaf(s[4].y, sc2, mb)));
            mma1688z(l2, one, one, p4);
            mma1688z(o1, vm0, vm1, p4);
            const float r0 = rcp(l[0] + l2[0]), r1 = rcp(l[1] + l2[1]);
            sts1(oa, pack2((o0[0] + o1[0]) * r0, (o0[1] + o1[1]) * r1));
            sts1(oa + 128, pack2((o0[2] + o1[2]) * r0, (o0[3] + o1[3]) * r1));
            bar_arrive_if_eq(BAR_B, 384, va, vma);
            if (__any_sync(0xffffffffu, va != vma)) {
                mbar_wait(sb + B_VM + wi * 8, ph);
                vm0 = lds1(vma); vm1 = lds1(vma + 128);
                mma1688z(o1, vm0, vm1, p4);
                sts1(oa, pack2((o0[0] + o1[0]) * r0, (o0[1] + o1[1]) * r1));
                sts1(oa + 128, pack2((o0[2] + o1[2]) * r0, (o0[3] + o1[3]) * r1));
                bar_arrive(BAR_B, 384);
            }
        }
        PROBE(6);
        if (wi == 3) {
            if (PUBPOS == 1 && j < VB_SEG) publish();
            fence_async_smem();
            if (j < VB_SEG && elect()) {
                bulk_s2g(gKV + ((size_t)j * 32 + head) * KV_BYTES + 8192 + half * 4096, sb + kvb + 5120, 4096);
                bulk_commit();
            }
            __syncwarp();
        }
        if (wi == 2 && j + 2 < NSEG) fetch_k(j + 2);
        if (l0) {
            if (wi == 0) mbar_expect(sb + B_SC, 1280);
            if (wi == 1) {
#pragma unroll
                for (int i = 0; i < NAG; i++) mbar_expect(sb + B_AG + i * 8, ag_size(i) * 512);
            }
        }
        __syncwarp();
        uint32_t tag = ((j >> 1) + 1) & 3;
        unsigned char* slot = gX + rank * 65536 + ph * 16384 + (wl4 - sb) * 2;
        unsigned char* g0 = slot + cid * 1024;
        if (HOME) { const float2 dd = lds2f(sb + DIST); slot += fbits(dd.x) > fbits(dd.y) ? 4096 : 0; }
        unsigned char* g1 = slot + (cid ^ 1) * 1024;
        unsigned char* g2 = slot + (cid ^ 2) * 1024; unsigned char* g3 = slot + (cid ^ 3) * 1024;
        uint32_t rsa = sb + RS + (wi >> 1) * 4096 + (wi & 1) * 128 + ((l8 - sb) >> 6) * 256 + ((l8 - sb) & 63) * 2;
        uint32_t sel = ((l8 - sb) >> 6) == (((l8 - sb) >> 3) & 3) ? 0x3f80u << (((l8 - sb) >> 1) & 16) : 0u;
        pin(g0); pin(g1); pin(g2); pin(g3); pin(tag); pin(rsa); pin(sel);
        float a0, a1;
        ag_addr();
        mbar_wait(sb + B_RS + (wi >> 1) * 8, ph);
        PROBE(7);
        {
            uint32_t r[4][4];
            float c0[4], c1[4], c2[4], c3[4];
#pragma unroll
            for (int t = 0; t < 4; t++) ldsm4(r[t], rsa + t * 1024);
            mma16816z(c0, r[0], sel, sel); mma16816z(c1, r[1], sel, sel);
            if (MSUM == 1) {
                mma16816(c0, r[2], sel, sel); mma16816(c1, r[3], sel, sel);
                a0 = (c0[0] + c0[2]) + (c1[0] + c1[2]);
                a1 = (c0[1] + c0[3]) + (c1[1] + c1[3]);
            } else {
                mma16816z(c2, r[2], sel, sel); mma16816z(c3, r[3], sel, sel);
                a0 = ((c0[0] + c0[2]) + (c1[0] + c1[2])) + ((c2[0] + c2[2]) + (c3[0] + c3[2]));
                a1 = ((c0[1] + c0[3]) + (c1[1] + c1[3])) + ((c2[1] + c2[3]) + (c3[1] + c3[3]));
            }
        }
        const uint32_t u0 = (__float_as_uint(a0) & ~3u) | tag;
        st_relaxed64(g0, u0, __float_as_uint(a1));
        if (HOME) st_relaxed64(g0 + 4096, u0, __float_as_uint(a1));
        if (NX1 < NXW) bar_arrive(BAR_E, 384);
        PROBE(8);
        if (!(wi & 1) && l0) mbar_expect(sb + B_RS + (wi >> 1) * 8, 4096);
        int n = 0;
        bool bad;
        const uint32_t c0 = clock_lo();
        if (PDELAY > 0) { while (clock_lo() - c0 < PDELAY) {} }
        uint64_t q1 = 0, q2 = 0, q3 = 0;
        auto check = [&](uint64_t r1, uint64_t r2, uint64_t r3) {
            const uint32_t x1 = (uint32_t)r1, x2 = (uint32_t)r2, x3 = (uint32_t)r3;
            bad = __any_sync(0xffffffffu, (((x1 ^ tag) | (x2 ^ tag) | (x3 ^ tag)) & 3) != 0);
            word = pack2((__uint_as_float(u0) + __uint_as_float(x1)) + (__uint_as_float(x2) + __uint_as_float(x3)),
                         (a1 + __uint_as_float((uint32_t)(r1 >> 32))) + (__uint_as_float((uint32_t)(r2 >> 32)) + __uint_as_float((uint32_t)(r3 >> 32))));
            pin(word);
        };
        if (PSTAG > 0) {
            while (true) {
                const uint64_t r1 = ld_relaxed64(g1), r2 = ld_relaxed64(g2), r3 = ld_relaxed64(g3);
                uint32_t z = clock_lo();
#pragma unroll
                for (int i = 0; i < PSTAG; i++) asm volatile("mad.lo.u32 %0, %0, %0, %0;" : "+r"(z));
                z &= l8 & 4;
                q1 = ld_relaxed64(g1 + z); q2 = ld_relaxed64(g2 + z); q3 = ld_relaxed64(g3 + z);
                check(r1, r2, r3);
                if (!bad) break;
                check(q1, q2, q3);
                if (!bad || ++n > (1 << 22)) break;
            }
        } else {
            do {
                const uint64_t r1 = ld_relaxed64(g1), r2 = ld_relaxed64(g2), r3 = ld_relaxed64(g3);
                check(r1, r2, r3);
                n++;
            } while (bad && n < (1 << 23));
        }
        PROBE(0);
        all_gather(word);
        if (PSTAG > 0) { sched_fence(l8 * 2); bad |= ((uint32_t)((q1 ^ q2 ^ q3) >> 32) & (uint32_t)(q1 ^ q2 ^ q3) & l8 & 4) != 0; }
        fault_if(bad);
    }
    cluster_arrive_relaxed();
    cluster_wait();
}

__global__ void __launch_bounds__(384, 1)
r_kernel(const __grid_constant__ CUtensorMap tmWq, const __grid_constant__ CUtensorMap tmWk, const __grid_constant__ CUtensorMap tmWv,
         const __grid_constant__ CUtensorMap tmWo, const __grid_constant__ CUtensorMap tmX, const __nv_bfloat16* __restrict__ mem0) {
    extern __shared__ __align__(1024) unsigned char smem[];
    const uint32_t sb = smem_u32(smem);
    uint32_t rank, cid;
    asm("mov.u32 %0, %%cluster_ctarank;" : "=r"(rank));
    asm("mov.u32 %0, %%clusterid.x;" : "=r"(cid));
    const int tid = threadIdx.x, lane = tid & 31;
    const int wg = __shfl_sync(0xffffffffu, tid >> 7, 0), wi = __shfl_sync(0xffffffffu, (tid >> 5) & 3, 0);
    asm volatile("griddepcontrol.launch_dependents;");
    const uint32_t epoch = ld_relaxed(&gDone) >> 6;
    const int head = cid * 8 + (rank >> 1);
    const uint32_t half = rank & 1;
    if (HOME && wg == 2 && wi < 2) st_relaxed(gX + rank * 65536 + 32768 + wi * 4096 + cid * 128 + lane * 4, 0);
    if (tid == 0) {
        mbar_init(sb + B_W1K, 1); mbar_init(sb + B_W1V, 1); mbar_init(sb + B_W2Q, 1); mbar_init(sb + B_W2O, 1);
        mbar_init(sb + B_X, 1); mbar_init(sb + B_X + 8, 1);
        for (int i = 0; i < NAG; i++) mbar_init(sb + B_AG + i * 8, 1);
        mbar_init(sb + B_SC, 1); mbar_init(sb + B_RS, 1); mbar_init(sb + B_RS + 8, 1); for (int i = 0; i < 4; i++) mbar_init(sb + B_VM + i * 8, 1);
        mbar_init(sb + B_KX, 1); mbar_init(sb + B_KX + 8, 1); mbar_arrive(sb + B_KX);
        mbar_expect(sb + B_W1K, 65536); mbar_expect(sb + B_W1V, 65536); mbar_expect(sb + B_W2Q, 65536); mbar_expect(sb + B_W2O, 65536);
        mbar_expect(sb + B_X, 32768);
#pragma unroll
        for (int i = 0; i < NAG; i++) mbar_expect(sb + B_AG + i * 8, ag_size(i) * 512);
        mbar_expect(sb + B_SC, 1280); mbar_expect(sb + B_RS, 4096); mbar_expect(sb + B_RS + 8, 4096);
        sts2(sb + DIST, 0x7fffffffu, 0x7fffffffu);
        static_assert(KR_SEG >= 2, "the first snapshot of the flags arrives with segment 1");
        asm volatile("fence.mbarrier_init.release.cluster;" ::: "memory");
    } else if (tid >= 32 && tid < 37) {
        prefetch_map(tid == 32 ? &tmWv : tid == 33 ? &tmWk : tid == 34 ? &tmX : tid == 35 ? &tmWq : &tmWo);
    }
    __syncthreads();
    cluster_arrive_relaxed();
    if (wg < 2) {
        const int col = head * 128 + half * 64, sl = wi * 4 + lane;
        if (lane < 4) tma2d(sb + (wg ? STG : WO) + sl * 4096, wg ? &tmWv : &tmWk, col, ((rank + sl) & 15) * 32, sb + (wg ? B_W1V : B_W1K));
        __syncwarp();
        bar_sync(BAR_F, 256);
        const int s2 = (wg * 4 + wi) * 2 + lane;
        if (lane < 2) tma2d(sb + XB + 32768 + s2 * 2048, &tmWq, col, ((rank + s2) & 15) * 32 + 16, sb + B_W2Q);
        __syncwarp();
    }
    cluster_wait();
    if (wg == 0) { reg_inc<REG0>(); compute_wg<0>(sb, rank, head, wi, lane, &tmWo); }
    else if (wg == 1) { reg_inc<REG1>(); compute_wg<1>(sb, rank, head, wi, lane, &tmWq); }
    else {
        reg_dec<REG2>();
        if (wi == 0 && lane == 0) {
            tma2d_mc(sb + XB + rank * 2048, &tmX, (rank >> 1) * 64, half * 16, sb + B_X, 0xffff);
            for (int i = 1; i < 4; i++) tma2d_prefetch(&tmX, (rank >> 1) * 64, i * 32 + half * 16);
        }
        __syncwarp();
        if (tid == 352) sts1(sb + EPOCH, epoch);
        comm_wg(sb, rank, cid, head, wi, lane, &tmX, mem0);
    }
}
}

namespace B {
#define PLL 1
#define LASTFULL 1
#define NGA 32
#define NGW 32
#define PSLEEP 0
constexpr uint32_t RES = 0, RING = 131072, KVS = RING + 57344, KVS_BYTES = 20480, MB = 229376, GATE = MB + 256, SMEM_BYTES = GATE + 1024;
constexpr uint32_t B_F = MB  , B_E = MB + 56  , B_R = MB + 112  ,
                   B_KVF = MB + 144  , B_KVE = MB + 160  , B_KMF = MB + 176  , B_KP = MB + 192  ;
constexpr int VT = 8;
constexpr uint32_t KPUB = 0x3084b;

DEVI void wait_counter(const uint32_t* p, uint32_t target) {
    int n = 0;
    while (__any_sync(0xffffffffu, (int)(ld_acquire(p) - target) < 0)) {
        if (++n > (1 << 23)) { fault_if(true); break; }
        if (PSLEEP) __nanosleep(PSLEEP); else if (n > 64) __nanosleep(100);
    }
}
DEVI void store_tile(unsigned char* base, const float (&d)[64]) {
#pragma unroll
    for (int i = 0; i < 8; i++) {
        const int o = (i & 3) * 16 + (i >> 2) * 2;
        *(uint4*)(base + i * 512) = make_uint4(pack2(d[o], d[o + 1]), pack2(d[o + 4], d[o + 5]), pack2(d[o + 8], d[o + 9]), pack2(d[o + 12], d[o + 13]));
    }
}

__global__ void __launch_bounds__(384, 1)
b_kernel(const __grid_constant__ CUtensorMap tmX, const __grid_constant__ CUtensorMap tmWg, const __grid_constant__ CUtensorMap tmWu,
         const __grid_constant__ CUtensorMap tmWd, const __grid_constant__ CUtensorMap tmWq, const __grid_constant__ CUtensorMap tmWo,
         const __grid_constant__ CUtensorMap tmWk, const __grid_constant__ CUtensorMap tmWv, const __nv_bfloat16* __restrict__ x,
         const __nv_bfloat16* __restrict__ gate_w, __nv_bfloat16* __restrict__ out) {
    extern __shared__ __align__(1024) unsigned char smem[];
    const uint32_t sb = smem_u32(smem);
    const int tid = threadIdx.x, lane = tid & 31;
    const int warp = __shfl_sync(0xffffffffu, tid >> 5, 0), wg = warp >> 2, wi = warp & 3;
    const int cta = blockIdx.x, pr = cta & 1, cl = cta >> 1;
    const uint32_t done = ld_relaxed(&gDone);
    const int head = (cl >> 1) * 2 + pr, par = cl & 1;
    const int rt = (cl >> 2) * 2 + pr, qd = cl & 3;
    const int hb0 = (qd >> 1) + 2 * (1 - par), nhb = par ? 6 : 5;
    const bool isA = par == 0;
    const int ks = cl >> 2, ns = (cl & 2) + pr;
    if (tid == 0 && cta == 0) TLS(1, 70);
    if (tid == 0) {
        for (int i = 0; i < 7; i++) { mbar_init(sb + B_F + i * 8, 1); mbar_init(sb + B_E + i * 8, 16); mbar_init(sb + B_KP + i * 8, 8); }
        for (int i = 0; i < 4; i++) { mbar_init(sb + B_R + i * 8, 1); mbar_expect(sb + B_R + i * 8, 131072); }
        for (int i = 0; i < 2; i++) { mbar_init(sb + B_KVF + i * 8, 1); mbar_init(sb + B_KVE + i * 8, 2); mbar_init(sb + B_KMF + i * 8, 4); }
        asm volatile("fence.mbarrier_init.release.cluster;" ::: "memory");
    }
    __syncthreads();
    cluster_arrive_relaxed();
    if (warp == 8 && elect()) {
#pragma unroll
        for (int i = 0; i < 16; i++) tma2d(sb + RES + i * 8192, &tmWk, head * 128 + (i >> 3) * 64, (i & 7) * 64, sb + B_R);
    }
    __syncwarp();
    cluster_wait();

    if (wg == 2) {
      reg_dec<56>();
      const uint32_t epoch = __shfl_sync(0xffffffffu, done >> 6, 0);
      if (warp == 8) {
        uint32_t eph = 0xffffffffu;
        auto acquire = [&](int st) { mbar_wait(sb + B_E + st * 8, (eph >> st) & 1); eph ^= 1u << st; };
        auto load_w = [&](const CUtensorMap* tm, int col, int row, int n, int i) {
            tma2d(sb + RES + i * 8192, tm, col + (i >> 3) * 64, row + (i & 7) * 64, sb + B_R + n * 8);
        };
        int st = 0;
#pragma unroll 1
        for (int it = 0; it < 68; it++) {
            const int t = it >> 2;
            acquire(st);
            if (elect()) {
                mbar_expect(sb + B_F + st * 8, 16384);
                tma2d_mc(sb + RING + st * 16384 + pr * 8192, &tmX, ((it & 3) * 2 + pr) * 64, ((t == VT ? 15 : t - (t > VT)) * 2 + par) * 64, sb + B_F + st * 8, 3);
            }
            st = st == 5 ? 0 : st + 1;
            if (it == 6 || it == 4 * VT + 10) bar_sync(1, 288);
            if (elect()) {
                if (it >= 14 && it < 30) load_w(&tmWv, head * 128, 0, 1, it - 14);
                if (it >= 48 && it < 64) tma2d(sb + RES + (it - 48) * 8192, &tmX, (it & 7) * 64, rt * 128 + ((it - 48) >> 3) * 64, sb + B_R + 16);
                if (it >= 32 && it < 43) {
                    const int bx = (it - 32) * 16 + (cta >> 2);
                    if ((cta & 3) == 0) tma2d_prefetch(&tmWg, (bx >> 3) * 64, (bx & 7) * 64);
                    else if ((cta & 3) == 1) tma2d_prefetch(&tmWu, (bx >> 3) * 64, (bx & 7) * 64);
                    else tma2d_prefetch(&tmWd, (bx & 7) * 64, (bx >> 3) * 64 + pr * 32);
                }
            }
        }
        const CUtensorMap* tmGU = pr ? &tmWu : &tmWg;
        const CUtensorMap* tmQO = isA ? &tmWq : &tmWo;
#pragma unroll 1
        for (int it = 0; it < nhb * 8; it++) {
            acquire(st);
            if (elect()) {
                mbar_expect(sb + B_F + st * 8, 16384);
                tma2d_mc(sb + RING + st * 16384 + pr * 8192, tmGU, (hb0 + (it >> 3) * 4) * 64, (it & 7) * 64, sb + B_F + st * 8, 3);
            }
            st = st == 5 ? 0 : st + 1;
            if (it == 6) bar_sync(1, 288);
            if (it >= 8 && !(it & 1) && it < 40 && elect()) load_w(tmQO, isA ? head * 128 : ns * 128, isA ? 0 : ks * 512, 3, (it - 8) >> 1);
        }
        if (isA) {
#pragma unroll 1
            for (int i = 0; i < 6; i++) mbar_wait(sb + B_E + i * 8, (eph >> i) & 1);
            st = 0;
#pragma unroll 1
            for (int it = 0; it < NGA * 8; it++) {
                acquire(st);
                if (elect()) {
                    mbar_expect(sb + B_F + st * 8, 8192);
                    if ((it & 1) == pr) tma2d_mc(sb + RING + st * 8192, &tmX, (it & 7) * 64, (it >> 3) * 64, sb + B_F + st * 8, 3);
                }
                st = st == 6 ? 0 : st + 1;
            }
        } else {
#pragma unroll 1
            for (int it = 0; it < 86; it++) {
                const int kb = it < 43 ? it : it - 43;
                acquire(st);
                if (elect()) {
                    mbar_expect(sb + B_F + st * 8, 16384);
                    tma2d_mc(sb + RING + st * 16384 + pr * 4096, &tmWd, ((cl & 2) + (it >= 43)) * 128 + pr * 64, kb * 32, sb + B_F + st * 8, 3);
                }
                st = st == 5 ? 0 : st + 1;
            }
            uint32_t seen = epoch * 32;
#pragma unroll 1
            for (int it = 0; it < NGW * 4; it++) {
                const uint32_t need = epoch * 32 + (it >> 2) + 1;
                if (__any_sync(0xffffffffu, (lane & 3) == (it & 3) && (int)(seen - need) < 0)) {
                    int n = 0;
                    do { if (PSLEEP && n && it < 120) __nanosleep(PSLEEP); seen = ld_acquire(gFlagO + (ks * 4 + (lane & 3)) * 32); }
                    while (__any_sync(0xffffffffu, (lane & 3) == (it & 3) && (int)(seen - need) < 0) && ++n < (1 << 23));
                    fault_if(n >= (1 << 23));
                    fence_async_global();
                }
                acquire(st);
                if (elect()) {
                    mbar_expect(sb + B_F + st * 8, 16384);
                    bulk_g2s_mc(sb + RING + st * 16384 + pr * 8192, gO + ((it >> 2) * 32 + ks * 4 + (it & 3)) * 16384 + pr * 8192, 8192, sb + B_F + st * 8, 3);
                }
                st = st == 5 ? 0 : st + 1;
            }
        }
      } else if (warp == 9) {
#pragma unroll 1
        for (int t = 0, n = 0; t < 18; t++) {
            if (!((KPUB >> t) & 1)) continue;
            mbar_wait(sb + B_KP + n * 8, 0);
            n++;
            if (lane == 0) {
                if (t < 17) st_release(gFlagK + head * 32 + par * 4, epoch * 32 + t + (t < VT));
                else red_release(gCntH + rt * 32, 1);
            }
            if (lane == 0 && cta == 0 && (t == 0 || t == 16)) TLS(1, 73 + (t >> 4));
            __syncwarp();
        }
#pragma unroll 1
        for (int g = 0; g < (isA ? NGA : NGW); g++) {
            bar_sync(2, 160);
            if (lane == 0) {
                if (isA) st_release(gFlagO + head * 32, epoch * 32 + g + 1);
                else if (!PLL || g < 31) red_release(gCntP + (g * 4 + ns) * 32, 1);
                if (g == 0) atomicAdd(&gDone, 1);
                if (cta == 0 || cta == 2) TLS(1 + (cta >> 1), g);
            }
            __syncwarp();
        }
      } else if (warp == 10 && isA) {
        mbar_wait(sb + B_KP + 6 * 8, 0);
        wait_counter(gFlagK + head * 32 + (lane & 1) * 4, epoch * 32 + 16);
        fence_async_global();
        uint32_t seen = epoch * 64;
#pragma unroll 1
        for (int s = 0; s < NGA * 2; s++) {
            if (s < VB_SEG && __any_sync(0xffffffffu, (int)(seen - (epoch * 64 + s + 1)) < 0)) {
                int n = 0;
                do { if (n) __nanosleep(100); seen = ld_acquire(gFlagKV + (head * 2 + (lane & 1)) * 32); }
                while (__any_sync(0xffffffffu, (int)(seen - (epoch * 64 + s + 1)) < 0) && ++n < (1 << 22));
                fault_if(n >= (1 << 22));
                fence_async_global();
            }
            if (s >= 2) mbar_wait(sb + B_KVE + (s & 1) * 8, ((s >> 1) - 1) & 1);
            const bool ahead = __all_sync(0xffffffffu, (int)(seen - (epoch * 64 + s + 3)) >= 0);
            if (elect()) {
                mbar_expect(sb + B_KVF + (s & 1) * 8, KV_BYTES);
                bulk_g2s(sb + KVS + (s & 1) * KVS_BYTES, gKV + (size_t)(s * 32 + head) * KV_BYTES, KV_BYTES, sb + B_KVF + (s & 1) * 8);
                if (s + 2 < NSEG) bulk_prefetch(gKV + (size_t)((s + 2) * 32 + head) * KV_BYTES, ahead || s + 2 >= VB_SEG ? 16384 : 8192);
            }
        }
      } else if (warp == 10) {
        wait_counter(gCntH + rt * 32, (epoch + 1) * 4);
        fence_async_global();
#pragma unroll 1
        for (int it = 0, st = 2, ph = 0; it < 86; it++) {
            mbar_wait(sb + B_E + st * 8, ph);
            if (elect()) bulk_g2s(sb + RING + st * 16384 + 8192, gH + (rt * 44 + (it < 43 ? it : it - 43)) * 8192, 8192, sb + B_F + st * 8);
            if (++st == 6) { st = 0; ph ^= 1; }
        }
      }
      cluster_arrive_relaxed();
      cluster_wait();
      if (tid == 256) asm volatile("griddepcontrol.wait;" ::: "memory");
    } else {
        reg_inc<224>();
        const uint32_t epoch = __shfl_sync(0xffffffffu, done >> 6, 0);
        uint32_t fph = 0;
        auto wait_full = [&](int st) { mbar_wait(sb + B_F + st * 8, (fph >> st) & 1); fph ^= 1u << st; };
        auto release = [&](int st, uint32_t n) { if (lane < 2) mbar_arrive_cnt((sb ^ (lane << 24)) + B_E + st * 8, n); };
        int st = 0, sp_ = 0;
        auto next = [&](int n) { sp_ = st; st = st == n - 1 ? 0 : st + 1; };
        {
            uint32_t w[32][4];
            mbar_wait(sb + B_R, 0);
            const uint32_t wl = sb + RES + wg * 65536 + ((lane >> 4) * 8 + (lane & 7)) * 128 + (((wi * 2 + ((lane >> 3) & 1)) ^ (lane & 7)) << 4);
#pragma unroll
            for (int i = 0; i < 32; i++) ldsm4t(w[i], wl + i * 2048);
            fence_async_smem();
            bar_arrive(1, 288);
#pragma unroll 1
            for (int t = 0, npub = 0; t < 17; t++) {
                float acc[32];
                if (t == VT) {
                    mbar_wait(sb + B_R + 8, 0);
#pragma unroll 1
                    for (int c = 0; c < 4; c++) {
                        wait_full(st);
                        wg_fence();
#pragma unroll
                        for (int k = 0; k < 8; k++)
                            wgmma_n64_st(acc, mkdesc(sb + RES + wg * 65536 + (c * 8 + k) * 2048, 16, 1024, 1),
                                         mkdesc(sb + RING + st * 16384 + (k >> 2) * 8192 + (k & 3) * 32, 16, 1024, 1), c | k);
                        wg_commit();
                        if (c > 0) { wg_wait<1>(); release(sp_, 1); }
                        next(6);
                    }
                    wg_wait<0>();
                    bar_arrive(1, 288);
                } else {
#pragma unroll
                    for (int c = 0; c < 4; c++) {
                        wait_full(st);
                        wg_fence();
#pragma unroll
                        for (int k = 0; k < 8; k++)
                            wgmma_n64_rs(acc, w[c * 8 + k], mkdesc(sb + RING + st * 16384 + (k >> 2) * 8192 + (k & 3) * 32, 16, 1024, 1), c | k);
                        wg_commit();
                        if (c > 0) { wg_wait<1>(); release(sp_, 1); }
                        next(6);
                    }
                    wg_wait<0>();
                }
                release(sp_, 1);
                const int g = (t == VT ? 15 : t - (t > VT)) * 2 + par;
                unsigned char* dst = gKV + ((size_t)g * 64 + head) * KV_BYTES + (t == VT) * 8192 + wg * 4096 + wi * 1024 + lane * 4;
#pragma unroll
                for (int nn = 0; nn < 8; nn++) {
                    *(uint32_t*)(dst + (nn >> 2) * 32 * KV_BYTES + (nn & 3) * 128) = pack2(acc[4 * nn], acc[4 * nn + 1]);
                    *(uint32_t*)(dst + (nn >> 2) * 32 * KV_BYTES + (nn & 3) * 128 + 512) = pack2(acc[4 * nn + 2], acc[4 * nn + 3]);
                }
                if ((KPUB >> t) & 1) { __syncwarp(); if (lane == 0) mbar_arrive(sb + B_KP + npub * 8); npub++; }
            }
        }
        float d[64];
        {
            uint32_t xa[32][4];
            mbar_wait(sb + B_R + 16, 0);
            const uint32_t xl = sb + RES + wg * 65536 + (wi * 16 + (lane & 15)) * 128;
#pragma unroll
            for (int i = 0; i < 32; i++) ldsm4(xa[i], xl + (i >> 2) * 8192 + ((((i & 3) * 2 + (lane >> 4)) ^ (lane & 7)) << 4));
            fence_async_smem();
            bar_arrive(1, 288);
#pragma unroll 1
            for (int t = 0; t < nhb; t++) {
#pragma unroll
                for (int kb = 0; kb < 8; kb++) {
                    wait_full(st);
                    wg_fence();
#pragma unroll
                    for (int k = 0; k < 4; k++) wgmma_n128_rs(d, xa[kb * 4 + k], mkdesc(sb + RING + st * 16384 + k * 2048, 8192, 1024, 1), kb | k);
                    wg_commit();
                    if (kb > 0) { wg_wait<1>(); release(sp_, 1); }
                    next(6);
                }
                wg_wait<0>();
                release(sp_, 1);
                unsigned char* dst = gH + (rt * 22 + hb0 + t * 4) * 16384 + (wg * 8 + wi * 2) * 128 + lane * 4;
#pragma unroll
                for (int nc = 0; nc < 8; nc++) {
                    float h[4];
#pragma unroll
                    for (int i = 0; i < 4; i++) { const float g = d[4 * nc + i]; h[i] = __fdividef(g, 1.f + __expf(-g)) * d[32 + 4 * nc + i]; }
                    *(uint32_t*)(dst + nc * 2048) = pack2(h[0], h[1]);
                    *(uint32_t*)(dst + nc * 2048 + 128) = pack2(h[2], h[3]);
                }
            }
        }
        __syncwarp();
        if (lane == 0) mbar_arrive(sb + B_KP + 6 * 8);
        if (tid == 0 && cta == 2) TLS(1, 71);
        if (!isA) {
#pragma unroll 1
            for (int t = 0; t < 2; t++) {
#pragma unroll 1
                for (int kb = 0; kb < 43; kb++) {
                    wait_full(st);
                    if (tid == 0 && cta == 2 && kb == 0) TLS(1, 75 + t);
                    wg_fence();
#pragma unroll
                    for (int k = 0; k < 2; k++)
                        wgmma_n128_ss(d, mkdesc(sb + RING + st * 16384 + 8192 + wg * 1024 + k * 4096, 2048, 128, 0),
                                      mkdesc(sb + RING + st * 16384 + k * 2048, 4096, 1024, 1), kb | k);
                    wg_commit();
                    if (kb > 0) { wg_wait<1>(); release(sp_, 1); }
                    next(6);
                }
                wg_wait<0>();
                release(sp_, 1);
                store_tile(gP + (((rt * 2 + wg) * 4 + (cl & 2) + t) * 9 + 8) * 16384 + wi * 4096 + lane * 16, d);
            }
            bar_sync(5, 256);
            if (wg == 1 && lane == 0) red_release(gCntP + ((rt * 2 + (wi >> 1)) * 4 + (cl & 2) + (wi & 1)) * 32, 1);
            if (tid == 0 && cta == 2) TLS(1, 72);
        }

        if (isA && wg == 1) {
            mbar_wait(sb + B_KP + 6 * 8, 0);
            uint32_t seen = epoch * 64;
#pragma unroll 1
            for (int s = 0; s < NGA * 2; s++) {
                const uint32_t buf = sb + KVS + (s & 1) * KVS_BYTES;
                const uint4* src = gM + (s * 32 + head) * 512 + wi * 128 + lane;
                int n = 0;
                if (s < VB_SEG) {
                    while ((int)(seen - (epoch * 64 + s + 1)) < 0 && ++n < (1 << 22)) {
                        if (n > 1) __nanosleep(200);
                        seen = __shfl_sync(0xffffffffu, ld_relaxed(gFlagKV + (head * 2 + (wi & 1)) * 32), 0);
                    }
                } else if (s < NSEG - 1 || !LASTFULL) {
                    while (__any_sync(0xffffffffu, ld_relaxed(&src[96 - lane].y) != epoch + 1) && ++n < (1 << 22)) if (s < NSEG - 1) __nanosleep(100);
                }
                uint4 m[4];
                bool bad;
                do {
#pragma unroll
                    for (int i = 0; i < 4; i++) m[i] = ld_tagged(src + i * 32);
                    bad = false;
#pragma unroll
                    for (int i = 0; i < 4; i++) bad |= m[i].y != epoch + 1 || m[i].w != epoch + 1;
                    bad = __any_sync(0xffffffffu, bad);
                } while (bad && ++n < (1 << 22));
                fault_if(bad);
                if (s >= 2) mbar_wait(sb + B_KVE + (s & 1) * 8, ((s >> 1) - 1) & 1);
#pragma unroll
                for (int i = 0; i < 4; i++) { sts1(buf + 16384 + wi * 1024 + i * 256 + lane * 4, m[i].x); sts1(buf + 16384 + wi * 1024 + i * 256 + 128 + lane * 4, m[i].z); }
                __syncwarp();
                if (lane == 0) mbar_arrive(sb + B_KMF + (s & 1) * 8);
            }
        } else if (isA) {
            const float sc2 = 0.08838834764831845f * 1.4426950408889634f;
            const int sp = wi >> 1, rh = wi & 1;
            const uint32_t kv = sb + KVS + sp * KVS_BYTES;
            mbar_wait(sb + B_R + 24, 0);
            st = 0;
#pragma unroll 1
            for (int g = 0; g < NGA; g++) {
#pragma unroll 1
                for (int c = 0; c < 8; c++) {
                    wait_full(st);
                    wg_fence();
#pragma unroll
                    for (int k = 0; k < 4; k++)
                        wgmma_n128_ss(d, mkdesc(sb + RING + st * 8192 + k * 32, 16, 1024, 1), mkdesc(sb + RES + (c * 4 + k) * 2048, 65536, 1024, 1), c | k);
                    wg_commit();
                    if (c > 0) { wg_wait<1>(); release(sp_, 2); }
                    next(7);
                }
                wg_wait<0>();
                release(sp_, 2);
                uint32_t q[8][4];
#pragma unroll
                for (int k = 0; k < 8; k++)
#pragma unroll
                    for (int i = 0; i < 4; i++) q[k][i] = pack2(d[8 * k + 2 * i], d[8 * k + 2 * i + 1]);
                if (tid == 96 && cta == 0) TLS(4, g);
                mbar_wait(sb + B_KVF + sp * 8, g & 1);
                float s[5][4];
#pragma unroll
                for (int kk = 0; kk < 4; kk++) {
#pragma unroll
                    for (int t = 0; t < 4; t++) {
                        uint32_t b[4];
                        ldsm4t(b, kv + (kk * 4 + (lane >> 3)) * 512 + t * 128 + (lane & 7) * 16);
                        if (kk == 0) mma16816z(s[t], q[0], b[0], b[1]); else mma16816(s[t], q[2 * kk], b[0], b[1]);
                        mma16816(s[t], q[2 * kk + 1], b[2], b[3]);
                    }
                }
                mbar_wait(sb + B_KMF + sp * 8, g & 1);
                if (tid == 96 && cta == 0) TLS(5, g);
                {
                    float s2[4];
#pragma unroll
                    for (int kk = 0; kk < 4; kk++) {
                        uint32_t b[4];
                        ldsm4t(b, kv + 16384 + kk * 512 + lane * 16);
                        if (kk == 0) { mma16816z(s[4], q[0], b[0], b[1]); mma16816z(s2, q[1], b[2], b[3]); }
                        else { mma16816(s[4], q[2 * kk], b[0], b[1]); mma16816(s2, q[2 * kk + 1], b[2], b[3]); }
                    }
#pragma unroll
                    for (int i = 0; i < 4; i++) s[4][i] += s2[i];
                }
                const int r0 = rh * 16 + (lane >> 2), c0 = (lane & 3) * 2;
                float m0 = fmaxf(s[4][0], s[4][1]), m1 = fmaxf(s[4][2], s[4][3]);
#pragma unroll
                for (int t = 0; t < 4; t++) {
#pragma unroll
                    for (int i = 0; i < 4; i++) if (t * 8 + c0 + (i & 1) > r0 + (i >> 1) * 8) s[t][i] = -INFINITY;
                    m0 = fmaxf(m0, fmaxf(s[t][0], s[t][1])); m1 = fmaxf(m1, fmaxf(s[t][2], s[t][3]));
                }
                m0 = fmaxf(m0, __shfl_xor_sync(0xffffffffu, m0, 1)); m1 = fmaxf(m1, __shfl_xor_sync(0xffffffffu, m1, 1));
                m0 = fmaxf(m0, __shfl_xor_sync(0xffffffffu, m0, 2)); m1 = fmaxf(m1, __shfl_xor_sync(0xffffffffu, m1, 2));
                const float b0 = -m0 * sc2, b1 = -m1 * sc2;
                float l0 = 0.f, l1 = 0.f;
                uint32_t p[5][2];
#pragma unroll
                for (int t = 0; t < 5; t++) {
                    const float e0 = ex2(fmaf(s[t][0], sc2, b0)), e1 = ex2(fmaf(s[t][1], sc2, b0));
                    const float e2 = ex2(fmaf(s[t][2], sc2, b1)), e3 = ex2(fmaf(s[t][3], sc2, b1));
                    l0 += e0 + e1; l1 += e2 + e3;
                    p[t][0] = pack2(e0, e1); p[t][1] = pack2(e2, e3);
                }
                l0 += __shfl_xor_sync(0xffffffffu, l0, 1); l1 += __shfl_xor_sync(0xffffffffu, l1, 1);
                l0 += __shfl_xor_sync(0xffffffffu, l0, 2); l1 += __shfl_xor_sync(0xffffffffu, l1, 2);
                const float i0 = rcp(l0), i1 = rcp(l1);
                unsigned char* dst = gO + (g * 32 + head) * 16384 + wi * 256 + lane * 4;
#pragma unroll
                for (int e4 = 0; e4 < 4; e4++) {
                    uint32_t vm[4];
                    ldsm4(vm, kv + 16384 + 2048 + e4 * 512 + lane * 16);
#pragma unroll
                    for (int e = 0; e < 4; e++) {
                        uint32_t v[4];
                        ldsm4(v, kv + 8192 + (e4 * 4 + e) * 512 + lane * 16);
                        float o[4];
                        mma16816z(o, p[0][0], p[0][1], p[1][0], p[1][1], v[0], v[1]);
                        mma16816(o, p[2][0], p[2][1], p[3][0], p[3][1], v[2], v[3]);
                        mma1688(o, p[4][0], p[4][1], vm[e]);
                        *(uint32_t*)(dst + (e4 * 4 + e) * 1024) = pack2(o[0] * i0, o[1] * i0);
                        *(uint32_t*)(dst + (e4 * 4 + e) * 1024 + 128) = pack2(o[2] * i1, o[3] * i1);
                    }
                }
                __syncwarp();
                if (lane == 0) mbar_arrive(sb + B_KVE + sp * 8);
                if (tid == 96 && cta == 0) TLS(6, g);
                bar_sync(2, 160);
            }
        } else if (wg == 0) {
            mbar_wait(sb + B_R + 24, 0);
#pragma unroll 1
            for (int g = 0; g < NGW; g++) {
#pragma unroll 1
                for (int c = 0; c < 4; c++) {
                    wait_full(st);
                    wg_fence();
#pragma unroll
                    for (int k = 0; k < 8; k++)
                        wgmma_n128_ss(d, mkdesc(sb + RING + st * 16384 + k * 2048, 1024, 128, 0),
                                      mkdesc(sb + RES + (c * 8 + k) * 2048, 65536, 1024, 1), c | k);
                    wg_commit();
                    if (c > 0) { wg_wait<1>(); release(sp_, 2); }
                    next(6);
                }
                wg_wait<0>();
                release(sp_, 2);
                if (PLL && g == 31) {
#pragma unroll
                    for (int i = 0; i < 16; i++) {
                        const int o = ((i >> 1) & 3) * 16 + (i >> 3) * 2 + (i & 1) * 8;
                        st_tagged(gPL + (ns * 8 + ks) * 2048 + wi * 512 + i * 32 + lane, pack2(d[o], d[o + 1]), pack2(d[o + 4], d[o + 5]), epoch + 1);
                    }
                } else store_tile(gP + ((g * 4 + ns) * 9 + ks) * 16384 + wi * 4096 + lane * 16, d);
                if (PLL && g == 31) bar_arrive(6, 256);
                if (PLL == 2 && g == 29) {
#pragma unroll
                    for (int i = 0; i < 16; i++) st_tagged(gPL + (ns * 8 + ks) * 2048 + wi * 512 + i * 32 + lane, 0, 0, epoch);
                }
                if (tid == 0 && cta == 2) TLS(7, g);
                bar_sync(2, 160);
            }
        } else {
            {
                const int r = wi * 2 + (lane >> 4), nc = lane & 15;
                float gw[32];
#pragma unroll
                for (int i = 0; i < 4; i++) {
                    const uint4 w = __ldg((const uint4*)(gate_w + i * 128 + nc * 8));
                    gw[8 * i] = bf_lo(w.x); gw[8 * i + 1] = bf_hi(w.x); gw[8 * i + 2] = bf_lo(w.y); gw[8 * i + 3] = bf_hi(w.y);
                    gw[8 * i + 4] = bf_lo(w.z); gw[8 * i + 5] = bf_hi(w.z); gw[8 * i + 6] = bf_lo(w.w); gw[8 * i + 7] = bf_hi(w.w);
                }
#pragma unroll 8
                for (int g = 0; g < 32; g++) {
                    float z = 0.f;
#pragma unroll
                    for (int i = 0; i < 4; i++) {
                        const uint4 v = __ldg((const uint4*)(x + (g * 64 + ks * 8 + r) * 512 + i * 128 + nc * 8));
                        z += bf_lo(v.x) * gw[8 * i] + bf_hi(v.x) * gw[8 * i + 1] + bf_lo(v.y) * gw[8 * i + 2] + bf_hi(v.y) * gw[8 * i + 3]
                           + bf_lo(v.z) * gw[8 * i + 4] + bf_hi(v.z) * gw[8 * i + 5] + bf_lo(v.w) * gw[8 * i + 6] + bf_hi(v.w) * gw[8 * i + 7];
                    }
#pragma unroll
                    for (int o = 1; o < 16; o <<= 1) z += __shfl_xor_sync(0xffffffffu, z, o);
                    if (nc == 0) sts1(sb + GATE + (g * 8 + r) * 4, __float_as_uint(__fdividef(1.f, 1.f + __expf(-z))));
                }
                bar_sync(3, 128);
            }
            cluster_arrive_relaxed();
            uint32_t ready = 0;
#pragma unroll 1
            for (int g = 0; g < NGW; g++) {
                const float gt = __uint_as_float(lds1(sb + GATE + (g * 8 + (lane >> 2)) * 4)), gn = 1.f - gt;
                for (int n = 0; !((ready >> g) & 1); n++) {
                    if (n > 8 && g < 30) __nanosleep(200);
                    const bool look = lane >= g && lane < g + 3;
                    ready = __ballot_sync(0xffffffffu, look && (int)(ld_acquire(gCntP + ((look ? lane : g) * 4 + ns) * 32) - (epoch + 1) * (PLL && lane == 31 ? 1 : 9)) >= 0);
                    if (n > (1 << 22)) { fault_if(true); break; }
                }
                const unsigned char* src = gP + (g * 4 + ns) * 9 * 16384 + ks * 2048 + wi * 512 + lane * 16;
                uint4 v[9];
                if (PLL && g == 31) {
                    v[8] = __ldcg((const uint4*)(src + 8 * 16384));
                    const uint4* ll = gPL + ns * 8 * 2048 + ks * 256 + wi * 64 + lane;
                    bar_sync(6, 256);
                    bool bad;
                    int n = 0;
                    do {
                        bad = false;
#pragma unroll
                        for (int i = 0; i < 8; i++) {
                            const uint4 a = ld_tagged(ll + i * 2048), b = ld_tagged(ll + i * 2048 + 32);
                            bad |= a.y != epoch + 1 || a.w != epoch + 1 || b.y != epoch + 1 || b.w != epoch + 1;
                            v[i] = make_uint4(a.x, a.z, b.x, b.z);
                        }
                        bad = __any_sync(0xffffffffu, bad);
                    } while (bad && ++n < (1 << 22));
                    fault_if(bad);
                } else {
#pragma unroll
                    for (int i = 0; i < 9; i++) v[i] = __ldcg((const uint4*)(src + i * 16384));
                }
                float a[8];
#pragma unroll
                for (int i = 0; i < 8; i++) a[i] = 0.f;
#pragma unroll
                for (int i = 0; i < 8; i++) {
                    a[0] += bf_lo(v[i].x); a[1] += bf_hi(v[i].x); a[2] += bf_lo(v[i].y); a[3] += bf_hi(v[i].y);
                    a[4] += bf_lo(v[i].z); a[5] += bf_hi(v[i].z); a[6] += bf_lo(v[i].w); a[7] += bf_hi(v[i].w);
                }
                uint32_t o0 = pack2(gt * a[0] + gn * bf_lo(v[8].x), gt * a[1] + gn * bf_hi(v[8].x));
                uint32_t o1 = pack2(gt * a[2] + gn * bf_lo(v[8].y), gt * a[3] + gn * bf_hi(v[8].y));
                uint32_t o2 = pack2(gt * a[4] + gn * bf_lo(v[8].z), gt * a[5] + gn * bf_hi(v[8].z));
                uint32_t o3 = pack2(gt * a[6] + gn * bf_lo(v[8].w), gt * a[7] + gn * bf_hi(v[8].w));
                {
                    const bool b0 = lane & 1, b1 = lane & 2;
                    uint32_t t0 = __shfl_xor_sync(0xffffffffu, b0 ? o0 : o1, 1), t1 = __shfl_xor_sync(0xffffffffu, b0 ? o2 : o3, 1);
                    if (b0) { o0 = t0; o2 = t1; } else { o1 = t0; o3 = t1; }
                    t0 = __shfl_xor_sync(0xffffffffu, b1 ? o0 : o2, 2); t1 = __shfl_xor_sync(0xffffffffu, b1 ? o1 : o3, 2);
                    if (b1) { o0 = t0; o1 = t1; } else { o2 = t0; o3 = t1; }
                }
                *(uint4*)(out + (g * 64 + ks * 8 + (lane >> 2)) * 512 + ns * 128 + (wi * 4 + (lane & 3)) * 8) = make_uint4(o0, o1, o2, o3);
                if (tid == 128 && cta == 2) TLS(3, g);
            }
        }
        if (isA || wg == 0) cluster_arrive_relaxed();
        cluster_wait();
    }
}
}

typedef CUresult (*EncodeFn)(CUtensorMap*, CUtensorMapDataType, cuuint32_t, void*, const cuuint64_t*, const cuuint64_t*,
                             const cuuint32_t*, const cuuint32_t*, CUtensorMapInterleave, CUtensorMapSwizzle,
                             CUtensorMapL2promotion, CUtensorMapFloatOOBfill);

void make_map(EncodeFn enc, CUtensorMap* tm, const void* ptr, int nd, const cuuint64_t* dims, const cuuint64_t* strides, const cuuint32_t* box) {
    cuuint32_t es[3] = {1, 1, 1};
    enc(tm, CU_TENSOR_MAP_DATA_TYPE_BFLOAT16, nd, (void*)ptr, dims, strides, box, es, CU_TENSOR_MAP_INTERLEAVE_NONE,
        CU_TENSOR_MAP_SWIZZLE_128B, CU_TENSOR_MAP_L2_PROMOTION_L2_256B, CU_TENSOR_MAP_FLOAT_OOB_FILL_NONE);
}
void make_map2(EncodeFn enc, CUtensorMap* tm, const void* ptr, uint64_t cols, uint64_t rows, uint32_t bc, uint32_t br) {
    cuuint64_t dims[2] = {cols, rows}, strides[1] = {cols * 2};
    cuuint32_t box[2] = {bc, br};
    make_map(enc, tm, ptr, 2, dims, strides, box);
}
void make_map3(EncodeFn enc, CUtensorMap* tm, const void* ptr, uint64_t cols, uint64_t rows, uint32_t br, uint32_t bchunks) {
    cuuint64_t dims[3] = {64, rows, cols / 64}, strides[2] = {cols * 2, 128};
    cuuint32_t box[3] = {64, br, bchunks};
    make_map(enc, tm, ptr, 3, dims, strides, box);
}

}

extern "C" void kernel_launch(void* const* d_in, const int* in_sizes, int n_in, void* d_out, int out_size) {
    const __nv_bfloat16* x = (const __nv_bfloat16*)d_in[0];
    const __nv_bfloat16* mem0 = (const __nv_bfloat16*)d_in[1];
    static bool init = false;
    static CUtensorMap tmWq, tmWk, tmWv, tmWo, tmXr, tmXb, tmWg, tmWu, tmWd, tmWqb, tmWob, tmWkb, tmWvb;
    if (!init) {
        void* fn = nullptr;
        cudaDriverEntryPointQueryResult qr;
        cudaGetDriverEntryPoint("cuTensorMapEncodeTiled", &fn, cudaEnableDefault, &qr);
        EncodeFn enc = (EncodeFn)fn;
        make_map2(enc, &tmWq, d_in[2], 4096, 512, 64, 16);
        make_map2(enc, &tmWk, d_in[3], 4096, 512, 64, 32);
        make_map2(enc, &tmWv, d_in[4], 4096, 512, 64, 32);
        make_map2(enc, &tmWo, d_in[5], 512, 4096, 64, 64);
        make_map2(enc, &tmXr, x, 512, 2048, 64, 16);
        make_map2(enc, &tmXb, x, 512, 2048, 64, 64);
        make_map2(enc, &tmWg, d_in[8], 1376, 512, 64, 64);
        make_map2(enc, &tmWu, d_in[9], 1376, 512, 64, 64);
        make_map2(enc, &tmWd, d_in[10], 512, 1376, 64, 32);
        make_map2(enc, &tmWqb, d_in[2], 4096, 512, 64, 64);
        make_map2(enc, &tmWob, d_in[5], 512, 4096, 64, 64);
        make_map2(enc, &tmWkb, d_in[3], 4096, 512, 64, 64);
        make_map2(enc, &tmWvb, d_in[4], 4096, 512, 64, 64);
        cudaFuncSetAttribute(B::b_kernel, cudaFuncAttributeMaxDynamicSharedMemorySize, B::SMEM_BYTES);
        cudaFuncSetAttribute(R::r_kernel, cudaFuncAttributeMaxDynamicSharedMemorySize, R::SMEM_BYTES);
        cudaFuncSetAttribute(R::r_kernel, cudaFuncAttributeNonPortableClusterSizeAllowed, 1);
        init = true;
    }
    {
        cudaLaunchConfig_t cfg = {};
        cfg.gridDim = dim3(64); cfg.blockDim = dim3(384); cfg.dynamicSmemBytes = R::SMEM_BYTES; cfg.stream = cudaStreamPerThread;
        cudaLaunchAttribute at[1];
        at[0].id = cudaLaunchAttributeClusterDimension; at[0].val.clusterDim.x = 16; at[0].val.clusterDim.y = 1; at[0].val.clusterDim.z = 1;
        cfg.attrs = at; cfg.numAttrs = 1;
        cudaLaunchKernelEx(&cfg, R::r_kernel, tmWq, tmWk, tmWv, tmWo, tmXr, mem0);
    }
    {
        cudaLaunchConfig_t cfg = {};
        cfg.gridDim = dim3(64); cfg.blockDim = dim3(384); cfg.dynamicSmemBytes = B::SMEM_BYTES; cfg.stream = cudaStreamPerThread;
        cudaLaunchAttribute at[2];
        at[0].id = cudaLaunchAttributeProgrammaticStreamSerialization; at[0].val.programmaticStreamSerializationAllowed = 1;
        at[1].id = cudaLaunchAttributeClusterDimension; at[1].val.clusterDim.x = 2; at[1].val.clusterDim.y = 1; at[1].val.clusterDim.z = 1;
        cfg.attrs = at; cfg.numAttrs = 2;
        cudaLaunchKernelEx(&cfg, B::b_kernel, tmXb, tmWg, tmWu, tmWd, tmWqb, tmWob, tmWkb, tmWvb, x, (const __nv_bfloat16*)d_in[11], (__nv_bfloat16*)d_out);
    }
}
```
